```python
import torch

def _softmax(x, axis=-1):
    return torch.softmax(x, dim=axis)
def _gelu(x):
    return torch.nn.functional.gelu(x, approximate="tanh")
def _silu(x):
    return torch.nn.functional.silu(x)
def _sigmoid(x):
    return torch.sigmoid(x)
def _layernorm(x, axis=-1, eps=1e-5):
    m = x.mean(dim=axis, keepdim=True)
    v = x.var(dim=axis, keepdim=True, unbiased=False)
    return (x - m) / torch.sqrt(v + eps)
def _scatter_add(tgt, idx, src, axis=0):
    return tgt.clone().index_add_(axis, idx, src)
def _segment_sum(src, seg, n):
    out = torch.zeros((n,) + src.shape[1:], dtype=src.dtype)
    return out.index_add_(0, seg, src)
def _pad(x, pw):
    flat = tuple(v for pair in reversed(pw) for v in pair)
    return torch.nn.functional.pad(x, flat)

kernel_name = 'recurrent_scan__ssm_conv_h3__dense_activation_relu__prompt'

def setup_inputs():

    _w = (lambda a: (lambda t: t.to(torch.bfloat16) if t.is_floating_point() else t)(torch.as_tensor(a)))
    def _A_setup():
        B, S, D = 1, 2048, 640
        ks = 4
        return {
            "q": _w((lambda *s: torch.randn(*s, dtype=torch.bfloat16) * 0.05)(B, S, D)),
            "k": _w((lambda *s: torch.randn(*s, dtype=torch.bfloat16) * 0.2)(B, S, D)),
            "v": _w((lambda *s: torch.randn(*s, dtype=torch.bfloat16) * 0.2)(B, S, D)),
            "shift_k": _w((lambda *s: torch.randn(*s, dtype=torch.bfloat16) * 0.2)(D, ks) * 0.5),
            "ssm_k": _w((lambda *s: torch.randn(*s, dtype=torch.bfloat16) * 0.2)(D, S) * (1.0 / S ** 0.5)),
            "ssm_D": _w((lambda *s: torch.randn(*s, dtype=torch.bfloat16) * 0.2)(D)),
        }
    _A_in = _A_setup()

    def _B_setup():
        B, S, D, Dff = 1, 2048, 640, 1536
        return {
            "x": _w((lambda *s: torch.randn(*s, dtype=torch.bfloat16) * 0.05)(B, S, D)),
            "w1": _w((lambda *s: torch.randn(*s, dtype=torch.bfloat16) * 0.1)(D, Dff)),
            "w2": _w((lambda *s: torch.randn(*s, dtype=torch.bfloat16) * 0.1)(Dff, D)),
        }
    _B_in = _B_setup()

    return {
        "A_q": _A_in["q"],
        "A_k": _A_in["k"],
        "A_v": _A_in["v"],
        "A_shift_k": _A_in["shift_k"],
        "A_ssm_k": _A_in["ssm_k"],
        "A_ssm_D": _A_in["ssm_D"],
        "B_x": _B_in["x"],
        "B_w1": _B_in["w1"],
        "B_w2": _B_in["w2"],
    }

def reference(A_q, A_k, A_v, A_shift_k, A_ssm_k, A_ssm_D, B_x, B_w1, B_w2):
    def _A_ref(q, k, v, shift_k, ssm_k, ssm_D):
        B, S, D = q.shape
        ks = shift_k.shape[-1]
        k_pad = _pad(k, ((0, 0), (ks - 1, 0), (0, 0)))
        k_shift = torch.zeros_like(k)
        for t in range(ks):
            k_shift = k_shift + k_pad[:, t:t + S, :] * shift_k[:, ks - 1 - t][None, None, :]
        kv = k_shift * v
        L = 2 * S
        kv_pad = _pad(kv, ((0, 0), (0, S), (0, 0)))
        kf_pad = _pad(ssm_k, ((0, 0), (0, S)))
        kv_f = (lambda x, axes=(-2,-1): torch.fft.rfft2(x.float(), dim=axes))(kv_pad[:, None, :, :], axes=(1, 2))
        kf_f = (lambda x, axes=(-2,-1): torch.fft.rfft2(x.float(), dim=axes))(kf_pad[:, None, :], axes=(1, 2))
        kf_f = (lambda x, *d: x.permute(*d))(kf_f, 1, 2, 0)
        y_f = kv_f * kf_f[None, :, :, :]
        y = (lambda x, s, axes=(-2,-1): torch.fft.irfft2(x, s=s, dim=axes).to(torch.bfloat16))(y_f, (1, L), axes=(1, 2))[:, 0, :S, :]
        y = y + kv * ssm_D[None, None, :]
        return q * y

    def _B_ref(x, w1, w2):
        h = torch.einsum("bsd,df->bsf", x, w1)
        zero = torch.zeros_like(h)
        h = torch.maximum(h, zero)
        return torch.einsum("bsf,fd->bsd", h, w2)

    x = A_q
    xn = _layernorm(x, axis=-1)
    s = _A_ref(xn, A_k, A_v, A_shift_k, A_ssm_k, A_ssm_D)
    g = _silu(_B_ref(xn, B_w1, B_w2))
    return x + s * g
```

```cpp
#include <cuda_runtime.h>
#include <cuda_bf16.h>
#include <cuda.h>
#include <stdint.h>

namespace {

constexpr int S_ = 2048, D_ = 640, DFF_ = 1536;
constexpr int NCTA = 128;
constexpr int NTHREADS = 384;

__device__ __align__(1024) __nv_bfloat16 g_xn[S_ * D_];
__device__ __align__(1024) __nv_bfloat16 g_uT[D_ * S_];
__device__ __align__(1024) __nv_bfloat16 g_h[S_ * DFF_];
__device__ __align__(1024) __nv_bfloat16 g_y2T[D_ * S_];
__device__ __align__(128) unsigned int g_flags[512];
constexpr int FL_EPOCH = 0, FL_TICKET = 1, FL_ERR = 2, FL_XN = 32, FL_U = 64, FL_H = 128, FL_Y = 256;

constexpr int STAGE_BYTES = 40960;
constexpr int NSTAGE = 4;
constexpr int OFF_U = NSTAGE * STAGE_BYTES;
constexpr int U_ZPAD = 896;
constexpr int U_PITCH = U_ZPAD + 4096;
constexpr int OFF_HC = OFF_U + 5 * U_PITCH;
constexpr int HC_PITCH = 8448;
constexpr int HC1_OFF = 4288;
constexpr int OFF_BAR = OFF_HC + 5 * HC_PITCH;
constexpr int SMEM_BYTES = OFF_BAR + 128;
constexpr int PS_BYTES = 4 * 8 * 264 * 4;
constexpr int OFF_XB = OFF_U;
constexpr int OFF_YT = OFF_U + 40960;
constexpr int B_FULL = 0, B_EMPTY = 4, B_HFULL = 8, B_UFULL = 9, B_XFREE = 10, B_XFULL = 11, B_YFULL = 12, NBAR = 13;

__device__ __forceinline__ uint32_t smem_u32(const void* p) { return (uint32_t)__cvta_generic_to_shared(p); }
__device__ __forceinline__ void mbar_init(uint32_t a, int c) { asm volatile("mbarrier.init.shared::cta.b64 [%0], %1;" ::"r"(a), "r"(c)); }
__device__ __forceinline__ void mbar_expect_tx(uint32_t a, int b) { asm volatile("mbarrier.arrive.expect_tx.shared::cta.b64 _, [%0], %1;" ::"r"(a), "r"(b) : "memory"); }
__device__ __forceinline__ void mbar_arrive(uint32_t a) { asm volatile("mbarrier.arrive.shared::cta.b64 _, [%0];" ::"r"(a) : "memory"); }
__device__ __forceinline__ void mbar_arrive_remote(uint32_t a_cluster) { asm volatile("mbarrier.arrive.release.cluster.shared::cluster.b64 _, [%0];" ::"r"(a_cluster) : "memory"); }
__device__ __forceinline__ bool mbar_try(uint32_t a, int ph) {
    uint32_t ok;
    asm volatile("{\n.reg .pred p;\nmbarrier.try_wait.parity.shared::cta.b64 p, [%1], %2;\nselp.b32 %0, 1, 0, p;\n}\n" : "=r"(ok) : "r"(a), "r"(ph) : "memory");
    return ok;
}
__device__ __forceinline__ bool mbar_try_cluster(uint32_t a, int ph) {
    uint32_t ok;
    asm volatile("{\n.reg .pred p;\nmbarrier.try_wait.parity.acquire.cluster.shared::cta.b64 p, [%1], %2;\nselp.b32 %0, 1, 0, p;\n}\n" : "=r"(ok) : "r"(a), "r"(ph) : "memory");
    return ok;
}
constexpr long long WAIT_LIMIT = 60000000LL;
__device__ __noinline__ void wait_timeout() { atomicExch(&g_flags[FL_ERR], 1u); }
__device__ __forceinline__ void mbar_wait(uint32_t a, int ph) {
    if (mbar_try(a, ph)) return;
    long long t0 = clock64();
    while (!mbar_try(a, ph)) { if (clock64() - t0 > WAIT_LIMIT) { wait_timeout(); break; } }
}
__device__ __forceinline__ void mbar_wait_cluster(uint32_t a, int ph) {
    if (mbar_try_cluster(a, ph)) return;
    long long t0 = clock64();
    while (!mbar_try_cluster(a, ph)) { if (clock64() - t0 > WAIT_LIMIT) { wait_timeout(); break; } }
}
__device__ __forceinline__ unsigned ld_acquire(const unsigned* p) { unsigned v; asm volatile("ld.acquire.gpu.global.u32 %0, [%1];" : "=r"(v) : "l"(p) : "memory"); return v; }
__device__ __forceinline__ void st_release(unsigned* p, unsigned v) { asm volatile("st.release.gpu.global.u32 [%0], %1;" ::"l"(p), "r"(v) : "memory"); }
__device__ __forceinline__ void red_release_add(unsigned* p, unsigned v) { asm volatile("red.release.gpu.global.add.u32 [%0], %1;" ::"l"(p), "r"(v) : "memory"); }
__device__ __forceinline__ void flag_wait(const unsigned* p, unsigned target) {
    if ((int)(ld_acquire(p) - target) >= 0) return;
    long long t0 = clock64();
    while ((int)(ld_acquire(p) - target) < 0) { __nanosleep(32); if (clock64() - t0 > WAIT_LIMIT) { wait_timeout(); break; } }
}
__device__ __forceinline__ void fence_proxy_async() { asm volatile("fence.proxy.async;" ::: "memory"); }
__device__ __forceinline__ void fence_proxy_async_smem() { asm volatile("fence.proxy.async.shared::cta;" ::: "memory"); }
__device__ __forceinline__ void bar_sync(int id, int n) { asm volatile("bar.sync %0, %1;" ::"r"(id), "r"(n) : "memory"); }

__device__ __forceinline__ void tma_load_2d(uint32_t dst, const CUtensorMap* tm, uint32_t bar, int c0, int c1) {
    asm volatile("cp.async.bulk.tensor.2d.shared::cluster.global.mbarrier::complete_tx::bytes [%0], [%1, {%3, %4}], [%2];"
                 ::"r"(dst), "l"(tm), "r"(bar), "r"(c0), "r"(c1) : "memory");
}
__device__ __forceinline__ void tma_store_2d(const CUtensorMap* tm, uint32_t src, int c0, int c1) {
    asm volatile("cp.async.bulk.tensor.2d.global.shared::cta.bulk_group [%0, {%2, %3}], [%1];" ::"l"(tm), "r"(src), "r"(c0), "r"(c1) : "memory");
}
__device__ __forceinline__ void bulk_load(uint32_t dst, const void* src, int bytes, uint32_t bar) {
    asm volatile("cp.async.bulk.shared::cluster.global.mbarrier::complete_tx::bytes [%0], [%1], %2, [%3];" ::"r"(dst), "l"(src), "r"(bytes), "r"(bar) : "memory");
}
__device__ __forceinline__ void bulk_prefetch_l2(const void* src, int bytes) {
    asm volatile("cp.async.bulk.prefetch.L2.global [%0], %1;" ::"l"(src), "r"(bytes) : "memory");
}
__device__ __forceinline__ void bulk_commit() { asm volatile("cp.async.bulk.commit_group;" ::: "memory"); }
__device__ __forceinline__ void bulk_wait0() { asm volatile("cp.async.bulk.wait_group 0;" ::: "memory"); }

__device__ __forceinline__ uint64_t make_desc(uint32_t saddr, uint32_t lbo, uint32_t sbo, uint32_t swz) {
    uint64_t d = 0;
    d |= (uint64_t)((saddr & 0x3FFFF) >> 4);
    d |= (uint64_t)((lbo & 0x3FFFF) >> 4) << 16;
    d |= (uint64_t)((sbo & 0x3FFFF) >> 4) << 32;
    d |= (uint64_t)swz << 62;
    return d;
}
__device__ __forceinline__ void wg_fence() { asm volatile("wgmma.fence.sync.aligned;" ::: "memory"); }
__device__ __forceinline__ void wg_commit() { asm volatile("wgmma.commit_group.sync.aligned;" ::: "memory"); }
template <int N> __device__ __forceinline__ void wg_wait() { asm volatile("wgmma.wait_group.sync.aligned %0;" ::"n"(N) : "memory"); }
template <int R> __device__ __forceinline__ void reg_alloc() { asm volatile("setmaxnreg.inc.sync.aligned.u32 %0;" ::"n"(R)); }
template <int R> __device__ __forceinline__ void reg_dealloc() { asm volatile("setmaxnreg.dec.sync.aligned.u32 %0;" ::"n"(R)); }
__device__ __forceinline__ void stmatrix_x4(uint32_t addr, uint32_t r0, uint32_t r1, uint32_t r2, uint32_t r3) {
    asm volatile("stmatrix.sync.aligned.m8n8.x4.shared.b16 [%0], {%1, %2, %3, %4};" ::"r"(addr), "r"(r0), "r"(r1), "r"(r2), "r"(r3) : "memory");
}
__device__ __forceinline__ uint32_t lds32(uint32_t a) { uint32_t v; asm volatile("ld.shared.b32 %0, [%1];" : "=r"(v) : "r"(a)); return v; }
__device__ __forceinline__ uint4 lds128(uint32_t a) { uint4 v; asm volatile("ld.shared.v4.b32 {%0,%1,%2,%3}, [%4];" : "=r"(v.x), "=r"(v.y), "=r"(v.z), "=r"(v.w) : "r"(a)); return v; }
__device__ __forceinline__ void sts128(uint32_t a, uint4 v) { asm volatile("st.shared.v4.b32 [%0], {%1,%2,%3,%4};" ::"r"(a), "r"(v.x), "r"(v.y), "r"(v.z), "r"(v.w) : "memory"); }
__device__ __forceinline__ uint32_t pack_bf16(float lo, float hi) { __nv_bfloat162 t = __floats2bfloat162_rn(lo, hi); return *reinterpret_cast<uint32_t*>(&t); }
__device__ __forceinline__ float bf16r(float v) { return __bfloat162float(__float2bfloat16_rn(v)); }
__device__ __forceinline__ float bf_lo(uint32_t v) { return __uint_as_float(v << 16); }
__device__ __forceinline__ float bf_hi(uint32_t v) { return __uint_as_float(v & 0xffff0000u); }

__device__ __forceinline__ void wgmma_rs_n64(float* d, uint32_t a0, uint32_t a1, uint32_t a2, uint32_t a3, uint64_t db, int sd) {
  asm volatile("{\n.reg .pred p;\nsetp.ne.b32 p, %37, 0;\n"
    "wgmma.mma_async.sync.aligned.m64n64k16.f32.bf16.bf16 {%0, %1, %2, %3, %4, %5, %6, %7, %8, %9, %10, %11, %12, %13, %14, %15, %16, %17, %18, %19, %20, %21, %22, %23, %24, %25, %26, %27, %28, %29, %30, %31}, {%32, %33, %34, %35}, %36, p, 1, 1, 0;\n}\n"
    : "+f"(d[0]), "+f"(d[1]), "+f"(d[2]), "+f"(d[3]), "+f"(d[4]), "+f"(d[5]), "+f"(d[6]), "+f"(d[7]), "+f"(d[8]), "+f"(d[9]), "+f"(d[10]), "+f"(d[11]), "+f"(d[12]), "+f"(d[13]), "+f"(d[14]), "+f"(d[15]), "+f"(d[16]), "+f"(d[17]), "+f"(d[18]), "+f"(d[19]), "+f"(d[20]), "+f"(d[21]), "+f"(d[22]), "+f"(d[23]), "+f"(d[24]), "+f"(d[25]), "+f"(d[26]), "+f"(d[27]), "+f"(d[28]), "+f"(d[29]), "+f"(d[30]), "+f"(d[31])
    : "r"(a0), "r"(a1), "r"(a2), "r"(a3), "l"(db), "r"(sd));
}
__device__ __forceinline__ void wgmma_ss_tb_n192(float* d, uint64_t da, uint64_t db, int sd) {
  asm volatile("{\n.reg .pred p;\nsetp.ne.b32 p, %98, 0;\n"
    "wgmma.mma_async.sync.aligned.m64n192k16.f32.bf16.bf16 {%0, %1, %2, %3, %4, %5, %6, %7, %8, %9, %10, %11, %12, %13, %14, %15, %16, %17, %18, %19, %20, %21, %22, %23, %24, %25, %26, %27, %28, %29, %30, %31, %32, %33, %34, %35, %36, %37, %38, %39, %40, %41, %42, %43, %44, %45, %46, %47, %48, %49, %50, %51, %52, %53, %54, %55, %56, %57, %58, %59, %60, %61, %62, %63, %64, %65, %66, %67, %68, %69, %70, %71, %72, %73, %74, %75, %76, %77, %78, %79, %80, %81, %82, %83, %84, %85, %86, %87, %88, %89, %90, %91, %92, %93, %94, %95}, %96, %97, p, 1, 1, 0, 1;\n}\n"
    : "+f"(d[0]), "+f"(d[1]), "+f"(d[2]), "+f"(d[3]), "+f"(d[4]), "+f"(d[5]), "+f"(d[6]), "+f"(d[7]), "+f"(d[8]), "+f"(d[9]), "+f"(d[10]), "+f"(d[11]), "+f"(d[12]), "+f"(d[13]), "+f"(d[14]), "+f"(d[15]), "+f"(d[16]), "+f"(d[17]), "+f"(d[18]), "+f"(d[19]), "+f"(d[20]), "+f"(d[21]), "+f"(d[22]), "+f"(d[23]), "+f"(d[24]), "+f"(d[25]), "+f"(d[26]), "+f"(d[27]), "+f"(d[28]), "+f"(d[29]), "+f"(d[30]), "+f"(d[31]), "+f"(d[32]), "+f"(d[33]), "+f"(d[34]), "+f"(d[35]), "+f"(d[36]), "+f"(d[37]), "+f"(d[38]), "+f"(d[39]), "+f"(d[40]), "+f"(d[41]), "+f"(d[42]), "+f"(d[43]), "+f"(d[44]), "+f"(d[45]), "+f"(d[46]), "+f"(d[47]), "+f"(d[48]), "+f"(d[49]), "+f"(d[50]), "+f"(d[51]), "+f"(d[52]), "+f"(d[53]), "+f"(d[54]), "+f"(d[55]), "+f"(d[56]), "+f"(d[57]), "+f"(d[58]), "+f"(d[59]), "+f"(d[60]), "+f"(d[61]), "+f"(d[62]), "+f"(d[63]), "+f"(d[64]), "+f"(d[65]), "+f"(d[66]), "+f"(d[67]), "+f"(d[68]), "+f"(d[69]), "+f"(d[70]), "+f"(d[71]), "+f"(d[72]), "+f"(d[73]), "+f"(d[74]), "+f"(d[75]), "+f"(d[76]), "+f"(d[77]), "+f"(d[78]), "+f"(d[79]), "+f"(d[80]), "+f"(d[81]), "+f"(d[82]), "+f"(d[83]), "+f"(d[84]), "+f"(d[85]), "+f"(d[86]), "+f"(d[87]), "+f"(d[88]), "+f"(d[89]), "+f"(d[90]), "+f"(d[91]), "+f"(d[92]), "+f"(d[93]), "+f"(d[94]), "+f"(d[95])
    : "l"(da), "l"(db), "r"(sd));
}
__device__ __forceinline__ void wgmma_ss_tb_n160(float* d, uint64_t da, uint64_t db, int sd) {
  asm volatile("{\n.reg .pred p;\nsetp.ne.b32 p, %82, 0;\n"
    "wgmma.mma_async.sync.aligned.m64n160k16.f32.bf16.bf16 {%0, %1, %2, %3, %4, %5, %6, %7, %8, %9, %10, %11, %12, %13, %14, %15, %16, %17, %18, %19, %20, %21, %22, %23, %24, %25, %26, %27, %28, %29, %30, %31, %32, %33, %34, %35, %36, %37, %38, %39, %40, %41, %42, %43, %44, %45, %46, %47, %48, %49, %50, %51, %52, %53, %54, %55, %56, %57, %58, %59, %60, %61, %62, %63, %64, %65, %66, %67, %68, %69, %70, %71, %72, %73, %74, %75, %76, %77, %78, %79}, %80, %81, p, 1, 1, 0, 1;\n}\n"
    : "+f"(d[0]), "+f"(d[1]), "+f"(d[2]), "+f"(d[3]), "+f"(d[4]), "+f"(d[5]), "+f"(d[6]), "+f"(d[7]), "+f"(d[8]), "+f"(d[9]), "+f"(d[10]), "+f"(d[11]), "+f"(d[12]), "+f"(d[13]), "+f"(d[14]), "+f"(d[15]), "+f"(d[16]), "+f"(d[17]), "+f"(d[18]), "+f"(d[19]), "+f"(d[20]), "+f"(d[21]), "+f"(d[22]), "+f"(d[23]), "+f"(d[24]), "+f"(d[25]), "+f"(d[26]), "+f"(d[27]), "+f"(d[28]), "+f"(d[29]), "+f"(d[30]), "+f"(d[31]), "+f"(d[32]), "+f"(d[33]), "+f"(d[34]), "+f"(d[35]), "+f"(d[36]), "+f"(d[37]), "+f"(d[38]), "+f"(d[39]), "+f"(d[40]), "+f"(d[41]), "+f"(d[42]), "+f"(d[43]), "+f"(d[44]), "+f"(d[45]), "+f"(d[46]), "+f"(d[47]), "+f"(d[48]), "+f"(d[49]), "+f"(d[50]), "+f"(d[51]), "+f"(d[52]), "+f"(d[53]), "+f"(d[54]), "+f"(d[55]), "+f"(d[56]), "+f"(d[57]), "+f"(d[58]), "+f"(d[59]), "+f"(d[60]), "+f"(d[61]), "+f"(d[62]), "+f"(d[63]), "+f"(d[64]), "+f"(d[65]), "+f"(d[66]), "+f"(d[67]), "+f"(d[68]), "+f"(d[69]), "+f"(d[70]), "+f"(d[71]), "+f"(d[72]), "+f"(d[73]), "+f"(d[74]), "+f"(d[75]), "+f"(d[76]), "+f"(d[77]), "+f"(d[78]), "+f"(d[79])
    : "l"(da), "l"(db), "r"(sd));
}
#define CONV_MMA_CHAIN(acc, A, db) \
  wgmma_rs_n64((acc) + 0, (A)[0], (A)[1], (A)[2], (A)[3], (db) + (0), 0); \
  wgmma_rs_n64((acc) + 32, (A)[0], (A)[1], (A)[2], (A)[3], (db) + (64), 0); \
  wgmma_rs_n64((acc) + 64, (A)[0], (A)[1], (A)[2], (A)[3], (db) + (128), 0); \
  wgmma_rs_n64((acc) + 96, (A)[0], (A)[1], (A)[2], (A)[3], (db) + (192), 0); \
  wgmma_rs_n64((acc) + 0, (A)[4], (A)[5], (A)[6], (A)[7], (db) + (-16), 1); \
  wgmma_rs_n64((acc) + 32, (A)[4], (A)[5], (A)[6], (A)[7], (db) + (48), 1); \
  wgmma_rs_n64((acc) + 64, (A)[4], (A)[5], (A)[6], (A)[7], (db) + (112), 1); \
  wgmma_rs_n64((acc) + 96, (A)[4], (A)[5], (A)[6], (A)[7], (db) + (176), 1); \
  wgmma_rs_n64((acc) + 0, (A)[8], (A)[9], (A)[10], (A)[11], (db) + (-32), 1); \
  wgmma_rs_n64((acc) + 32, (A)[8], (A)[9], (A)[10], (A)[11], (db) + (32), 1); \
  wgmma_rs_n64((acc) + 64, (A)[8], (A)[9], (A)[10], (A)[11], (db) + (96), 1); \
  wgmma_rs_n64((acc) + 96, (A)[8], (A)[9], (A)[10], (A)[11], (db) + (160), 1); \
  wgmma_rs_n64((acc) + 0, (A)[12], (A)[13], (A)[14], (A)[15], (db) + (-48), 1); \
  wgmma_rs_n64((acc) + 32, (A)[12], (A)[13], (A)[14], (A)[15], (db) + (16), 1); \
  wgmma_rs_n64((acc) + 64, (A)[12], (A)[13], (A)[14], (A)[15], (db) + (80), 1); \
  wgmma_rs_n64((acc) + 96, (A)[12], (A)[13], (A)[14], (A)[15], (db) + (144), 1); \
  wgmma_rs_n64((acc) + 32, (A)[16], (A)[17], (A)[18], (A)[19], (db) + (0), 1); \
  wgmma_rs_n64((acc) + 64, (A)[16], (A)[17], (A)[18], (A)[19], (db) + (64), 1); \
  wgmma_rs_n64((acc) + 96, (A)[16], (A)[17], (A)[18], (A)[19], (db) + (128), 1); \
  wgmma_rs_n64((acc) + 32, (A)[20], (A)[21], (A)[22], (A)[23], (db) + (-16), 1); \
  wgmma_rs_n64((acc) + 64, (A)[20], (A)[21], (A)[22], (A)[23], (db) + (48), 1); \
  wgmma_rs_n64((acc) + 96, (A)[20], (A)[21], (A)[22], (A)[23], (db) + (112), 1); \
  wgmma_rs_n64((acc) + 32, (A)[24], (A)[25], (A)[26], (A)[27], (db) + (-32), 1); \
  wgmma_rs_n64((acc) + 64, (A)[24], (A)[25], (A)[26], (A)[27], (db) + (32), 1); \
  wgmma_rs_n64((acc) + 96, (A)[24], (A)[25], (A)[26], (A)[27], (db) + (96), 1); \
  wgmma_rs_n64((acc) + 32, (A)[28], (A)[29], (A)[30], (A)[31], (db) + (-48), 1); \
  wgmma_rs_n64((acc) + 64, (A)[28], (A)[29], (A)[30], (A)[31], (db) + (16), 1); \
  wgmma_rs_n64((acc) + 96, (A)[28], (A)[29], (A)[30], (A)[31], (db) + (80), 1); \
  wgmma_rs_n64((acc) + 64, (A)[32], (A)[33], (A)[34], (A)[35], (db) + (0), 1); \
  wgmma_rs_n64((acc) + 96, (A)[32], (A)[33], (A)[34], (A)[35], (db) + (64), 1); \
  wgmma_rs_n64((acc) + 64, (A)[36], (A)[37], (A)[38], (A)[39], (db) + (-16), 1); \
  wgmma_rs_n64((acc) + 96, (A)[36], (A)[37], (A)[38], (A)[39], (db) + (48), 1); \
  wgmma_rs_n64((acc) + 64, (A)[40], (A)[41], (A)[42], (A)[43], (db) + (-32), 1); \
  wgmma_rs_n64((acc) + 96, (A)[40], (A)[41], (A)[42], (A)[43], (db) + (32), 1); \
  wgmma_rs_n64((acc) + 64, (A)[44], (A)[45], (A)[46], (A)[47], (db) + (-48), 1); \
  wgmma_rs_n64((acc) + 96, (A)[44], (A)[45], (A)[46], (A)[47], (db) + (16), 1); \
  wgmma_rs_n64((acc) + 96, (A)[48], (A)[49], (A)[50], (A)[51], (db) + (0), 1); \
  wgmma_rs_n64((acc) + 96, (A)[52], (A)[53], (A)[54], (A)[55], (db) + (-16), 1); \
  wgmma_rs_n64((acc) + 96, (A)[56], (A)[57], (A)[58], (A)[59], (db) + (-32), 1); \
  wgmma_rs_n64((acc) + 96, (A)[60], (A)[61], (A)[62], (A)[63], (db) + (-48), 1);

struct KParams {
    const __nv_bfloat16 *x, *k, *v, *shift_k, *ssm_k, *ssm_D, *w1, *w2;
    __nv_bfloat16* out;
};

__global__ void __launch_bounds__(NTHREADS, 1)
fused_kernel(const __grid_constant__ CUtensorMap tm_xn, const __grid_constant__ CUtensorMap tm_w1,
             const __grid_constant__ CUtensorMap tm_h, const __grid_constant__ CUtensorMap tm_w2,
             const __grid_constant__ CUtensorMap tm_y2T, const KParams P) {
    extern __shared__ __align__(1024) uint8_t smem[];
    const uint32_t sb = smem_u32(smem);
    const uint32_t bars = sb + OFF_BAR;
    const int tid = threadIdx.x, lane = tid & 31, warp = tid >> 5, wg = tid >> 7;
    const int cta = blockIdx.x;
    const int rb = cta >> 3;
    const int jn = cta & 7;
    const int kh = cta & 1;
    const int cb = (cta >> 1) & 3;

    if (tid == 0) {
        for (int i = 0; i < 4; i++) { mbar_init(bars + 8 * (B_FULL + i), 1); mbar_init(bars + 8 * (B_EMPTY + i), 8); }
        mbar_init(bars + 8 * B_HFULL, 1); mbar_init(bars + 8 * B_UFULL, 1);
        mbar_init(bars + 8 * B_XFREE, 256); mbar_init(bars + 8 * B_XFULL, 256); mbar_init(bars + 8 * B_YFULL, 1);
        asm volatile("fence.mbarrier_init.release.cluster;" ::: "memory");
    }
    if (tid < 280) { *reinterpret_cast<uint4*>(smem + OFF_U + (tid / 56) * U_PITCH + (tid % 56) * 16) = make_uint4(0, 0, 0, 0); }
    if (tid >= 192 && tid < 192 + 10) { int i = tid - 192; *reinterpret_cast<uint4*>(smem + OFF_HC + (i >> 1) * HC_PITCH + (i & 1) * HC1_OFF) = make_uint4(0, 0, 0, 0); }
    fence_proxy_async_smem();
    const unsigned epoch = ld_acquire(&g_flags[FL_EPOCH]);
    const unsigned ep1 = epoch + 1;
    __syncthreads();
    asm volatile("barrier.cluster.arrive.release.aligned;\nbarrier.cluster.wait.acquire.aligned;" ::: "memory");

    if (wg == 0) {
        reg_dealloc<40>();
        if (warp == 0 && lane == 0) {
            mbar_expect_tx(bars + 8 * B_HFULL, 5 * 4096);
            for (int ch = 0; ch < 5; ch++)
                bulk_load(sb + OFF_HC + ch * HC_PITCH + 16, P.ssm_k + (size_t)(cta * 5 + ch) * S_, 4096, bars + 8 * B_HFULL);
            int it = 0;
            for (int kb = 0; kb < 4; kb++) {
                uint32_t st = sb + kb * STAGE_BYTES;
                mbar_expect_tx(bars + 8 * (B_FULL + kb), 16384 + 24576);
                for (int q = 0; q < 3; q++) tma_load_2d(st + 16384 + q * 8192, &tm_w1, bars + 8 * (B_FULL + kb), jn * 192 + q * 64, kb * 64);
            }
            bulk_prefetch_l2(reinterpret_cast<const uint8_t*>(P.w2) + (size_t)cta * 15360, 15360);
            flag_wait(&g_flags[FL_XN + rb], 8u * ep1);
            fence_proxy_async();
            for (int kb = 0; kb < 4; kb++) tma_load_2d(sb + kb * STAGE_BYTES, &tm_xn, bars + 8 * (B_FULL + kb), kb * 64, rb * 128);
            it = 4;
            for (int kb = 4; kb < 10; kb++, it++) {
                int s = it & 3;
                mbar_wait(bars + 8 * (B_EMPTY + s), ((it >> 2) - 1) & 1);
                uint32_t st = sb + s * STAGE_BYTES;
                mbar_expect_tx(bars + 8 * (B_FULL + s), 16384 + 24576);
                for (int q = 0; q < 3; q++) tma_load_2d(st + 16384 + q * 8192, &tm_w1, bars + 8 * (B_FULL + s), jn * 192 + q * 64, kb * 64);
                tma_load_2d(st, &tm_xn, bars + 8 * (B_FULL + s), kb * 64, rb * 128);
            }
            flag_wait(&g_flags[FL_U], (unsigned)NCTA * ep1);
            fence_proxy_async();
            mbar_expect_tx(bars + 8 * B_UFULL, 5 * 4096);
            for (int ch = 0; ch < 5; ch++)
                bulk_load(sb + OFF_U + ch * U_PITCH + U_ZPAD, g_uT + (size_t)(cta * 5 + ch) * S_, 4096, bars + 8 * B_UFULL);
            for (int q = 0; q < 4; q++) flag_wait(&g_flags[FL_H + rb * 8 + kh * 4 + q], ep1);
            fence_proxy_async();
            for (int kb = 0; kb < 12; kb++, it++) {
                int s = it & 3;
                mbar_wait(bars + 8 * (B_EMPTY + s), ((it >> 2) - 1) & 1);
                uint32_t st = sb + s * STAGE_BYTES;
                mbar_expect_tx(bars + 8 * (B_FULL + s), 16384 + 20480);
                for (int q = 0; q < 5; q++) tma_load_2d(st + 16384 + q * 4096, &tm_w2, bars + 8 * (B_FULL + s), cb * 160 + q * 32, kh * 768 + kb * 64);
                tma_load_2d(st, &tm_h, bars + 8 * (B_FULL + s), kh * 768 + kb * 64, rb * 128);
            }
            for (int q = 0; q < 16; q++) flag_wait(&g_flags[FL_Y + cb * 32 + kh * 16 + q], ep1);
            fence_proxy_async();
            mbar_expect_tx(bars + 8 * B_YFULL, 20480);
            for (int q = 0; q < 2; q++) tma_load_2d(sb + OFF_YT + q * 10240, &tm_y2T, bars + 8 * B_YFULL, rb * 128 + q * 64, cb * 160 + kh * 80);
        }
    } else {
        reg_alloc<232>();
        const int ct = tid - 128;
        const int cw = ct >> 5;
        const int wgc = wg - 1;
        const int w4 = cw & 3;
        const int g4 = lane >> 2, c4 = lane & 3;

        {
            #pragma unroll
            for (int rr = 0; rr < 2; rr++) {
                int row = cta * 16 + cw * 2 + rr;
                const uint2* xr = reinterpret_cast<const uint2*>(P.x + (size_t)row * D_);
                uint2 v[5];
                #pragma unroll
                for (int q = 0; q < 5; q++) v[q] = __ldg(xr + q * 32 + lane);
                float f[20];
                #pragma unroll
                for (int q = 0; q < 5; q++) { f[4*q] = bf_lo(v[q].x); f[4*q+1] = bf_hi(v[q].x); f[4*q+2] = bf_lo(v[q].y); f[4*q+3] = bf_hi(v[q].y); }
                float s = 0.f;
                #pragma unroll
                for (int i = 0; i < 20; i++) s += f[i];
                #pragma unroll
                for (int o = 16; o; o >>= 1) s += __shfl_xor_sync(0xffffffffu, s, o);
                float mean = s * (1.0f / 640.0f);
                float vs = 0.f;
                #pragma unroll
                for (int i = 0; i < 20; i++) { float d = f[i] - mean; vs += d * d; }
                #pragma unroll
                for (int o = 16; o; o >>= 1) vs += __shfl_xor_sync(0xffffffffu, vs, o);
                float mb = bf16r(mean);
                float vb = bf16r(vs * (1.0f / 640.0f));
                float den = bf16r(sqrtf(bf16r(vb + 1e-5f)));
                uint2* xo = reinterpret_cast<uint2*>(g_xn + (size_t)row * D_);
                #pragma unroll
                for (int q = 0; q < 5; q++) {
                    float a0 = bf16r(f[4*q] - mb) , a1 = bf16r(f[4*q+1] - mb), a2 = bf16r(f[4*q+2] - mb), a3 = bf16r(f[4*q+3] - mb);
                    uint2 o; o.x = pack_bf16(__fdiv_rn(a0, den), __fdiv_rn(a1, den)); o.y = pack_bf16(__fdiv_rn(a2, den), __fdiv_rn(a3, den));
                    xo[q * 32 + lane] = o;
                }
            }
            __threadfence();
            bar_sync(1, 256);
            if (ct == 0) red_release_add(&g_flags[FL_XN + rb], 1u);
        }
        if (ct < 160) {
            const int c0 = ct * 4;
            const int t0 = cta * 16;
            uint2 kk[19], vv[16];
            #pragma unroll
            for (int i = 0; i < 19; i++) {
                int t = t0 - 3 + i;
                kk[i] = (t >= 0) ? __ldg(reinterpret_cast<const uint2*>(P.k + (size_t)t * D_ + c0)) : make_uint2(0, 0);
            }
            #pragma unroll
            for (int i = 0; i < 16; i++) vv[i] = __ldg(reinterpret_cast<const uint2*>(P.v + (size_t)(t0 + i) * D_ + c0));
            uint4 wa = __ldg(reinterpret_cast<const uint4*>(P.shift_k + c0 * 4));
            uint4 wb = __ldg(reinterpret_cast<const uint4*>(P.shift_k + c0 * 4 + 8));
            uint32_t wp[2][4];
            wp[0][0] = __byte_perm(wa.x, wa.z, 0x5410); wp[0][1] = __byte_perm(wa.x, wa.z, 0x7632);
            wp[0][2] = __byte_perm(wa.y, wa.w, 0x5410); wp[0][3] = __byte_perm(wa.y, wa.w, 0x7632);
            wp[1][0] = __byte_perm(wb.x, wb.z, 0x5410); wp[1][1] = __byte_perm(wb.x, wb.z, 0x7632);
            wp[1][2] = __byte_perm(wb.y, wb.w, 0x5410); wp[1][3] = __byte_perm(wb.y, wb.w, 0x7632);
            uint32_t u[2][16];
            #pragma unroll
            for (int i = 0; i < 16; i++) {
                #pragma unroll
                for (int p = 0; p < 2; p++) {
                    auto ld = [&](int idx) { uint32_t r = p ? kk[idx].y : kk[idx].x; return *reinterpret_cast<__nv_bfloat162*>(&r); };
                    auto wv = [&](int d) { return *reinterpret_cast<__nv_bfloat162*>(&wp[p][d]); };
                    __nv_bfloat162 a = __hmul2_rn(ld(i), wv(3));
                    a = __hadd2_rn(a, __hmul2_rn(ld(i + 1), wv(2)));
                    a = __hadd2_rn(a, __hmul2_rn(ld(i + 2), wv(1)));
                    a = __hadd2_rn(a, __hmul2_rn(ld(i + 3), wv(0)));
                    uint32_t vr = p ? vv[i].y : vv[i].x;
                    a = __hmul2_rn(a, *reinterpret_cast<__nv_bfloat162*>(&vr));
                    u[p][i] = *reinterpret_cast<uint32_t*>(&a);
                }
            }
            #pragma unroll
            for (int p = 0; p < 2; p++) {
                #pragma unroll
                for (int e = 0; e < 2; e++) {
                    const uint32_t sel = e ? 0x7632 : 0x5410;
                    __nv_bfloat16* dst = g_uT + (size_t)(c0 + 2 * p + e) * S_ + t0;
                    #pragma unroll
                    for (int g = 0; g < 2; g++) {
                        uint4 o;
                        o.x = __byte_perm(u[p][8*g+7], u[p][8*g+6], sel);
                        o.y = __byte_perm(u[p][8*g+5], u[p][8*g+4], sel);
                        o.z = __byte_perm(u[p][8*g+3], u[p][8*g+2], sel);
                        o.w = __byte_perm(u[p][8*g+1], u[p][8*g+0], sel);
                        *reinterpret_cast<uint4*>(dst + 8 * g) = o;
                    }
                }
            }
            __threadfence();
        }
        bar_sync(1, 256);
        if (ct == 0) red_release_add(&g_flags[FL_U], 1u);

        mbar_wait(bars + 8 * B_HFULL, 0);
        #pragma unroll
        for (int ch = 0; ch < 5; ch++) {
            uint32_t b0 = sb + OFF_HC + ch * HC_PITCH + 16;
            uint4 a = lds128(b0 + ct * 16);
            uint32_t nx = (ct < 255) ? lds32(b0 + ct * 16 + 16) : 0u;
            uint4 o;
            o.x = __byte_perm(a.x, a.y, 0x5432); o.y = __byte_perm(a.y, a.z, 0x5432); o.z = __byte_perm(a.z, a.w, 0x5432); o.w = __byte_perm(a.w, nx, 0x5432);
            sts128(sb + OFF_HC + ch * HC_PITCH + HC1_OFF + 16 + ct * 16, o);
            if (ct == 0) {
                uint32_t h0 = a.x & 0xffffu;
                asm volatile("st.shared.b32 [%0], %1;" ::"r"(sb + OFF_HC + ch * HC_PITCH + HC1_OFF + 12), "r"(h0 << 16) : "memory");
            }
        }

        int it = 0;
        {
            float acc[96];
            #pragma unroll
            for (int kb = 0; kb < 10; kb++, it++) {
                int s = it & 3;
                mbar_wait(bars + 8 * (B_FULL + s), (it >> 2) & 1);
                uint32_t st = sb + s * STAGE_BYTES;
                uint64_t da = make_desc(st + wgc * 8192, 16, 1024, 1);
                uint64_t db = make_desc(st + 16384, 8192, 1024, 1);
                wg_fence();
                #pragma unroll
                for (int k = 0; k < 4; k++) wgmma_ss_tb_n192(acc, da + k * 2, db + k * 128, (kb | k) ? 1 : 0);
                wg_commit();
                if (kb > 0) {
                    wg_wait<1>();
                    if (kb - 1 < 8 && lane == 0) mbar_arrive(bars + 8 * (B_EMPTY + ((it - 1) & 3)));
                }
            }
            wg_wait<0>();
            bar_sync(1, 256);
            #pragma unroll
            for (int j = 0; j < 24; j += 2) {
                uint32_t r0 = pack_bf16(fmaxf(acc[4*j], 0.f), fmaxf(acc[4*j+1], 0.f));
                uint32_t r1 = pack_bf16(fmaxf(acc[4*j+2], 0.f), fmaxf(acc[4*j+3], 0.f));
                uint32_t r2 = pack_bf16(fmaxf(acc[4*j+4], 0.f), fmaxf(acc[4*j+5], 0.f));
                uint32_t r3 = pack_bf16(fmaxf(acc[4*j+6], 0.f), fmaxf(acc[4*j+7], 0.f));
                int mat = lane >> 3;
                int row = wgc * 64 + w4 * 16 + (lane & 7) + (mat & 1) * 8;
                int colg = j + (mat >> 1);
                int box = colg >> 3, cc = colg & 7;
                uint32_t addr = sb + box * 16384 + row * 128 + ((cc ^ (row & 7)) << 4);
                stmatrix_x4(addr, r0, r1, r2, r3);
            }
            fence_proxy_async_smem();
            bar_sync(1, 256);
            if (ct == 0) {
                for (int q = 0; q < 3; q++) tma_store_2d(&tm_h, sb + q * 16384, jn * 192 + q * 64, rb * 128);
                bulk_commit();
                bulk_wait0();
                __threadfence();
                st_release(&g_flags[FL_H + cta], ep1);
            }
            bar_sync(1, 256);
        }

        {
            mbar_wait(bars + 8 * B_UFULL, 0);
            const uint32_t ps = sb + wgc * PS_BYTES;
            const int par = (g4 + 1) & 1;
            for (int ch = wgc; ch < 5; ch += 2) {
                const uint32_t hbase = sb + OFF_HC + ch * HC_PITCH;
                const uint32_t pb = hbase + (par ? (HC1_OFF + 16 - 2) : 16) + 2 * (16 * w4 + g4 - 7 + 2 * c4);
                uint32_t A[64];
                #pragma unroll
                for (int g2 = 0; g2 < 16; g2++) {
                    A[4*g2+0] = lds32(pb + 128 * (2*g2+1));
                    A[4*g2+1] = lds32(pb + 128 * (2*g2+1) + 16);
                    A[4*g2+2] = lds32(pb + 128 * (2*g2));
                    A[4*g2+3] = lds32(pb + 128 * (2*g2) + 16);
                }
                float acc[128];
                const uint64_t db = make_desc(sb + OFF_U + ch * U_PITCH + U_ZPAD - 128, 128, 128, 0);
                wg_fence();
                CONV_MMA_CHAIN(acc, A, db);
                wg_commit();
                wg_wait<0>();
                float prev = 0.f;
                const uint32_t dst = ps + ((w4 * 8 + g4) * 264 + 2 * w4 + 2 * c4) * 4;
                #pragma unroll
                for (int j = 0; j < 32; j++) {
                    float send = (c4 == 3) ? prev : acc[4*j+3];
                    prev = acc[4*j+3];
                    float got = __shfl_sync(0xffffffffu, send, (lane & ~3) | ((c4 + 3) & 3));
                    float p0 = acc[4*j] + got, p1 = acc[4*j+1] + acc[4*j+2];
                    asm volatile("st.shared.v2.f32 [%0], {%1, %2};" ::"r"(dst + j * 32), "f"(p0), "f"(p1) : "memory");
                }
                bar_sync(2 + wgc, 128);
                const float Dc = __bfloat162float(P.ssm_D[cta * 5 + ch]);
                const int t128 = ct & 127;
                #pragma unroll
                for (int hh = 0; hh < 2; hh++) {
                    int a = t128 + 128 * hh;
                    uint4 ub = lds128(sb + OFF_U + ch * U_PITCH + U_ZPAD + a * 16);
                    uint32_t uw[4] = {ub.x, ub.y, ub.z, ub.w};
                    float y2[8];
                    #pragma unroll
                    for (int b = 0; b < 8; b++) {
                        uint32_t ad = ps + (b * 264 + a) * 4;
                        float y = __uint_as_float(lds32(ad));
                        float y1 = __uint_as_float(lds32(ad + 8 * 264 * 4));
                        float y2_ = __uint_as_float(lds32(ad + 16 * 264 * 4));
                        float y3 = __uint_as_float(lds32(ad + 24 * 264 * 4));
                        if (hh == 0) { if (a < 2) y1 = 0.f; if (a < 4) y2_ = 0.f; if (a < 6) y3 = 0.f; }
                        float yy = (y + y1) + (y2_ + y3);
                        int e = 7 - b;
                        float uu = (e & 1) ? bf_hi(uw[e >> 1]) : bf_lo(uw[e >> 1]);
                        y2[b] = bf16r(bf16r(yy) + bf16r(uu * Dc));
                    }
                    uint4 o; o.x = pack_bf16(y2[0], y2[1]); o.y = pack_bf16(y2[2], y2[3]); o.z = pack_bf16(y2[4], y2[5]); o.w = pack_bf16(y2[6], y2[7]);
                    *reinterpret_cast<uint4*>(g_y2T + (size_t)(cta * 5 + ch) * S_ + 8 * a) = o;
                }
                bar_sync(2 + wgc, 128);
            }
            __threadfence();
            bar_sync(1, 256);
            if (ct == 0) st_release(&g_flags[FL_Y + cta], ep1);
            {
                uint32_t peer_bar;
                asm volatile("mapa.shared::cluster.u32 %0, %1, %2;" : "=r"(peer_bar) : "r"(bars + 8 * B_XFREE), "r"(kh ^ 1));
                mbar_arrive_remote(peer_bar);
            }
            if (lane == 0) { mbar_arrive(bars + 8 * (B_EMPTY + 0)); mbar_arrive(bars + 8 * (B_EMPTY + 1)); }
        }

        {
            float acc[80];
            for (int kb = 0; kb < 12; kb++, it++) {
                int s = it & 3;
                mbar_wait(bars + 8 * (B_FULL + s), (it >> 2) & 1);
                uint32_t st = sb + s * STAGE_BYTES;
                uint64_t da = make_desc(st + wgc * 8192, 16, 1024, 1);
                uint64_t db = make_desc(st + 16384, 4096, 512, 2);
                wg_fence();
                #pragma unroll
                for (int k = 0; k < 4; k++) wgmma_ss_tb_n160(acc, da + k * 2, db + k * 64, (kb | k) ? 1 : 0);
                wg_commit();
                if (kb > 0) {
                    wg_wait<1>();
                    if (lane == 0) mbar_arrive(bars + 8 * (B_EMPTY + ((it - 1) & 3)));
                }
            }
            wg_wait<0>();
            mbar_wait_cluster(bars + 8 * B_XFREE, 0);
            {
                uint32_t xb_peer, bar_peer;
                asm volatile("mapa.shared::cluster.u32 %0, %1, %2;" : "=r"(xb_peer) : "r"(sb + OFF_XB), "r"(kh ^ 1));
                asm volatile("mapa.shared::cluster.u32 %0, %1, %2;" : "=r"(bar_peer) : "r"(bars + 8 * B_XFULL), "r"(kh ^ 1));
                const int so = (kh ^ 1) * 40;
                #pragma unroll
                for (int i = 0; i < 10; i++) {
                    float v0 = kh ? acc[4*i] : acc[40+4*i], v1 = kh ? acc[4*i+1] : acc[40+4*i+1], v2 = kh ? acc[4*i+2] : acc[40+4*i+2], v3 = kh ? acc[4*i+3] : acc[40+4*i+3];
                    asm volatile("st.shared::cluster.v4.f32 [%0], {%1,%2,%3,%4};" ::"r"(xb_peer + (i * 256 + ct) * 16), "f"(v0), "f"(v1), "f"(v2), "f"(v3) : "memory");
                }
                (void)so;
                mbar_arrive_remote(bar_peer);
            }
            const int col0 = cb * 160 + kh * 80;
            mbar_wait_cluster(bars + 8 * B_XFULL, 0);
            mbar_wait(bars + 8 * B_YFULL, 0);
            #pragma unroll
            for (int i = 0; i < 10; i++) {
                uint4 r = lds128(sb + OFF_XB + (i * 256 + ct) * 16);
                float z[4];
                z[0] = (kh ? acc[40+4*i] : acc[4*i]) + __uint_as_float(r.x);
                z[1] = (kh ? acc[40+4*i+1] : acc[4*i+1]) + __uint_as_float(r.y);
                z[2] = (kh ? acc[40+4*i+2] : acc[4*i+2]) + __uint_as_float(r.z);
                z[3] = (kh ? acc[40+4*i+3] : acc[4*i+3]) + __uint_as_float(r.w);
                #pragma unroll
                for (int hf = 0; hf < 2; hf++) {
                    int rl = wgc * 64 + w4 * 16 + g4 + hf * 8;
                    int row = rb * 128 + rl;
                    int cl = 8 * i + 2 * c4;
                    uint32_t xw = *reinterpret_cast<const uint32_t*>(P.x + (size_t)row * D_ + col0 + cl);
                    uint32_t xnw = *reinterpret_cast<const uint32_t*>(g_xn + (size_t)row * D_ + col0 + cl);
                    float res[2];
                    #pragma unroll
                    for (int e = 0; e < 2; e++) {
                        int chl = cl + e; int box = rl >> 6, tl = rl & 63;
                        uint32_t ya = sb + OFF_YT + box * 10240 + chl * 128 + ((((tl >> 3) ^ (chl & 7)) << 4) | ((tl & 7) << 1));
                        uint32_t yv; asm volatile("ld.shared.u16 %0, [%1];" : "=r"(yv) : "r"(ya));
                        float y2 = __uint_as_float(yv << 16);
                        float zb = bf16r(z[2 * hf + e]);
                        float g = bf16r(__fdividef(zb, 1.0f + __expf(-zb)));
                        float xnv = e ? bf_hi(xnw) : bf_lo(xnw);
                        float xv = e ? bf_hi(xw) : bf_lo(xw);
                        float sv = bf16r(xnv * y2);
                        res[e] = xv + bf16r(sv * g);
                    }
                    *reinterpret_cast<uint32_t*>(P.out + (size_t)row * D_ + col0 + cl) = pack_bf16(res[0], res[1]);
                }
            }
        }
    }
    __syncthreads();
    if (tid == 0) {
        __threadfence();
        unsigned t = atomicAdd(&g_flags[FL_TICKET], 1u);
        if (t == NCTA - 1) { g_flags[FL_TICKET] = 0; __threadfence(); st_release(&g_flags[FL_EPOCH], ep1); }
    }
}

typedef CUresult (*EncFn)(CUtensorMap*, CUtensorMapDataType, cuuint32_t, void*, const cuuint64_t*, const cuuint64_t*, const cuuint32_t*, const cuuint32_t*,
                          CUtensorMapInterleave, CUtensorMapSwizzle, CUtensorMapL2promotion, CUtensorMapFloatOOBfill);

bool make_map_2d(EncFn enc, CUtensorMap* m, const void* ptr, uint64_t inner, uint64_t outer, uint32_t box_in, uint32_t box_out, CUtensorMapSwizzle swz) {
    cuuint64_t dims[2] = {inner, outer};
    cuuint64_t strides[1] = {inner * 2};
    cuuint32_t box[2] = {box_in, box_out};
    cuuint32_t es[2] = {1, 1};
    return enc(m, CU_TENSOR_MAP_DATA_TYPE_BFLOAT16, 2, const_cast<void*>(ptr), dims, strides, box, es, CU_TENSOR_MAP_INTERLEAVE_NONE, swz,
               CU_TENSOR_MAP_L2_PROMOTION_L2_128B, CU_TENSOR_MAP_FLOAT_OOB_FILL_NONE) == CUDA_SUCCESS;
}

}

extern "C" void kernel_launch(void* const* d_in, const int* in_sizes, int n_in, void* d_out, int out_size) {
    static EncFn enc = nullptr;
    if (!enc) {
        void* fn = nullptr; cudaDriverEntryPointQueryResult q;
        cudaGetDriverEntryPoint("cuTensorMapEncodeTiled", &fn, cudaEnableDefault, &q);
        enc = (EncFn)fn;
        cudaFuncSetAttribute(fused_kernel, cudaFuncAttributeMaxDynamicSharedMemorySize, SMEM_BYTES);
    }
    KParams P;
    P.x = (const __nv_bfloat16*)d_in[0]; P.k = (const __nv_bfloat16*)d_in[1]; P.v = (const __nv_bfloat16*)d_in[2];
    P.shift_k = (const __nv_bfloat16*)d_in[3]; P.ssm_k = (const __nv_bfloat16*)d_in[4]; P.ssm_D = (const __nv_bfloat16*)d_in[5];
    P.w1 = (const __nv_bfloat16*)d_in[7]; P.w2 = (const __nv_bfloat16*)d_in[8];
    P.out = (__nv_bfloat16*)d_out;
    void *p_xn, *p_h, *p_y2T;
    cudaGetSymbolAddress(&p_xn, g_xn); cudaGetSymbolAddress(&p_h, g_h); cudaGetSymbolAddress(&p_y2T, g_y2T);
    CUtensorMap tm_xn, tm_w1, tm_h, tm_w2, tm_y2T;
    make_map_2d(enc, &tm_xn, p_xn, D_, S_, 64, 128, CU_TENSOR_MAP_SWIZZLE_128B);
    make_map_2d(enc, &tm_w1, P.w1, DFF_, D_, 64, 64, CU_TENSOR_MAP_SWIZZLE_128B);
    make_map_2d(enc, &tm_h, p_h, DFF_, S_, 64, 128, CU_TENSOR_MAP_SWIZZLE_128B);
    make_map_2d(enc, &tm_w2, P.w2, D_, DFF_, 32, 64, CU_TENSOR_MAP_SWIZZLE_64B);
    make_map_2d(enc, &tm_y2T, p_y2T, S_, D_, 64, 80, CU_TENSOR_MAP_SWIZZLE_128B);

    cudaLaunchConfig_t cfg = {};
    cfg.gridDim = dim3(NCTA); cfg.blockDim = dim3(NTHREADS); cfg.dynamicSmemBytes = SMEM_BYTES; cfg.stream = cudaStreamPerThread;
    cudaLaunchAttribute at[1];
    at[0].id = cudaLaunchAttributeClusterDimension; at[0].val.clusterDim.x = 2; at[0].val.clusterDim.y = 1; at[0].val.clusterDim.z = 1;
    cfg.attrs = at; cfg.numAttrs = 1;
    cudaLaunchKernelEx(&cfg, fused_kernel, tm_xn, tm_w1, tm_h, tm_w2, tm_y2T, P);
}
```

```cpp
#include <cuda_runtime.h>
#include <cuda_bf16.h>
#include <cuda.h>
#include <stdint.h>

namespace {

constexpr int S_ = 2048, D_ = 640, DFF_ = 1536;
constexpr int NCTA = 128;
constexpr int NTHREADS = 384;

__device__ __align__(1024) __nv_bfloat16 g_xn[S_ * D_];
__device__ __align__(1024) __nv_bfloat16 g_uT[D_ * S_];
__device__ __align__(1024) __nv_bfloat16 g_h[S_ * DFF_];
__device__ __align__(1024) __nv_bfloat16 g_y2T[D_ * S_];
__device__ __align__(128) unsigned int g_flags[512];
#define TICK(i) do {} while (0)
constexpr int FL_EPOCH = 0, FL_TICKET = 1, FL_ERR = 2, FL_XN = 32, FL_U = 64, FL_H = 128, FL_Y = 256;

constexpr int STAGE_BYTES = 40960;
constexpr int NSTAGE = 4;
constexpr int OFF_U = NSTAGE * STAGE_BYTES;
constexpr int U_ZPAD = 896;
constexpr int U_PITCH = U_ZPAD + 4096;
constexpr int OFF_HC = OFF_U + 5 * U_PITCH;
constexpr int HC_PITCH = 8448;
constexpr int HC1_OFF = 4288;
constexpr int OFF_BAR = OFF_HC + 5 * HC_PITCH;
constexpr int SMEM_BYTES = OFF_BAR + 256;
constexpr int PS_BYTES = 4 * 8 * 264 * 4;
constexpr int OFF_XB = OFF_U;
constexpr int OFF_YT = OFF_U + 40960;
constexpr int B_FULL = 0, B_EMPTY = 4, B_HFULL = 8, B_UFULL = 9, B_XFREE = 10, B_XFULL = 11, B_YFULL = 12, B_HST = 13, B_STGFREE = 14, B_KVFULL = 15, B_KVFREE = 16, B_USIG = 17, B_YSIG = 18, NBAR = 19;
constexpr int OFF_KST = OFF_U, OFF_VST = OFF_U + 24576, OFF_UST = OFF_U + 45056;

__device__ __forceinline__ uint32_t smem_u32(const void* p) { return (uint32_t)__cvta_generic_to_shared(p); }
__device__ __forceinline__ void mbar_init(uint32_t a, int c) { asm volatile("mbarrier.init.shared::cta.b64 [%0], %1;" ::"r"(a), "r"(c)); }
__device__ __forceinline__ void mbar_expect_tx(uint32_t a, int b) { asm volatile("mbarrier.arrive.expect_tx.shared::cta.b64 _, [%0], %1;" ::"r"(a), "r"(b) : "memory"); }
__device__ __forceinline__ void mbar_arrive(uint32_t a) { asm volatile("mbarrier.arrive.shared::cta.b64 _, [%0];" ::"r"(a) : "memory"); }
__device__ __forceinline__ void mbar_arrive_remote(uint32_t a_cluster) { asm volatile("mbarrier.arrive.release.cluster.shared::cluster.b64 _, [%0];" ::"r"(a_cluster) : "memory"); }
__device__ __forceinline__ bool mbar_try(uint32_t a, int ph) {
    uint32_t ok;
    asm volatile("{\n.reg .pred p;\nmbarrier.try_wait.parity.shared::cta.b64 p, [%1], %2;\nselp.b32 %0, 1, 0, p;\n}\n" : "=r"(ok) : "r"(a), "r"(ph) : "memory");
    return ok;
}
__device__ __forceinline__ bool mbar_try_cluster(uint32_t a, int ph) {
    uint32_t ok;
    asm volatile("{\n.reg .pred p;\nmbarrier.try_wait.parity.acquire.cluster.shared::cta.b64 p, [%1], %2;\nselp.b32 %0, 1, 0, p;\n}\n" : "=r"(ok) : "r"(a), "r"(ph) : "memory");
    return ok;
}
constexpr long long WAIT_LIMIT = 60000000LL;
constexpr int SPIN_LIMIT = 1 << 22;
__device__ __forceinline__ void mbar_wait(uint32_t a, int ph) {
    #pragma unroll 1
    for (int i = 0; i < SPIN_LIMIT; i++) if (mbar_try(a, ph)) break;
}
__device__ __forceinline__ void mbar_wait_cluster(uint32_t a, int ph) {
    #pragma unroll 1
    for (int i = 0; i < SPIN_LIMIT; i++) if (mbar_try_cluster(a, ph)) break;
}
__device__ __forceinline__ unsigned ld_acquire(const unsigned* p) { unsigned v; asm volatile("ld.acquire.gpu.global.u32 %0, [%1];" : "=r"(v) : "l"(p) : "memory"); return v; }
__device__ __forceinline__ void st_release(unsigned* p, unsigned v) { asm volatile("st.release.gpu.global.u32 [%0], %1;" ::"l"(p), "r"(v) : "memory"); }
__device__ __forceinline__ void red_release_add(unsigned* p, unsigned v) { asm volatile("red.release.gpu.global.add.u32 [%0], %1;" ::"l"(p), "r"(v) : "memory"); }
__device__ __forceinline__ void flag_wait(const unsigned* p, unsigned target) {
    if ((int)(ld_acquire(p) - target) >= 0) return;
    long long t0 = clock64();
    while ((int)(ld_acquire(p) - target) < 0) { __nanosleep(20); if (clock64() - t0 > WAIT_LIMIT) { atomicExch(&g_flags[FL_ERR], 1u); break; } }
}
__device__ __forceinline__ void fence_proxy_async() { asm volatile("fence.proxy.async;" ::: "memory"); }
__device__ __forceinline__ void fence_proxy_async_smem() { asm volatile("fence.proxy.async.shared::cta;" ::: "memory"); }
__device__ __forceinline__ void bar_sync(int id, int n) { asm volatile("bar.sync %0, %1;" ::"r"(id), "r"(n) : "memory"); }

__device__ __forceinline__ void tma_load_2d(uint32_t dst, const CUtensorMap* tm, uint32_t bar, int c0, int c1) {
    asm volatile("cp.async.bulk.tensor.2d.shared::cluster.global.mbarrier::complete_tx::bytes [%0], [%1, {%3, %4}], [%2];"
                 ::"r"(dst), "l"(tm), "r"(bar), "r"(c0), "r"(c1) : "memory");
}
__device__ __forceinline__ void tma_store_2d(const CUtensorMap* tm, uint32_t src, int c0, int c1) {
    asm volatile("cp.async.bulk.tensor.2d.global.shared::cta.bulk_group [%0, {%2, %3}], [%1];" ::"l"(tm), "r"(src), "r"(c0), "r"(c1) : "memory");
}
__device__ __forceinline__ void bulk_load(uint32_t dst, const void* src, int bytes, uint32_t bar) {
    asm volatile("cp.async.bulk.shared::cluster.global.mbarrier::complete_tx::bytes [%0], [%1], %2, [%3];" ::"r"(dst), "l"(src), "r"(bytes), "r"(bar) : "memory");
}
__device__ __forceinline__ void bulk_prefetch_l2(const void* src, int bytes) {
    asm volatile("cp.async.bulk.prefetch.L2.global [%0], %1;" ::"l"(src), "r"(bytes) : "memory");
}
__device__ __forceinline__ void bulk_commit() { asm volatile("cp.async.bulk.commit_group;" ::: "memory"); }
__device__ __forceinline__ void bulk_wait0() { asm volatile("cp.async.bulk.wait_group 0;" ::: "memory"); }

__device__ __forceinline__ uint64_t make_desc(uint32_t saddr, uint32_t lbo, uint32_t sbo, uint32_t swz) {
    uint64_t d = 0;
    d |= (uint64_t)((saddr & 0x3FFFF) >> 4);
    d |= (uint64_t)((lbo & 0x3FFFF) >> 4) << 16;
    d |= (uint64_t)((sbo & 0x3FFFF) >> 4) << 32;
    d |= (uint64_t)swz << 62;
    return d;
}
__device__ __forceinline__ void wg_fence() { asm volatile("wgmma.fence.sync.aligned;" ::: "memory"); }
__device__ __forceinline__ void wg_commit() { asm volatile("wgmma.commit_group.sync.aligned;" ::: "memory"); }
template <int N> __device__ __forceinline__ void wg_wait() { asm volatile("wgmma.wait_group.sync.aligned %0;" ::"n"(N) : "memory"); }
template <int R> __device__ __forceinline__ void reg_alloc() { asm volatile("setmaxnreg.inc.sync.aligned.u32 %0;" ::"n"(R)); }
template <int R> __device__ __forceinline__ void reg_dealloc() { asm volatile("setmaxnreg.dec.sync.aligned.u32 %0;" ::"n"(R)); }
__device__ __forceinline__ void stmatrix_x4(uint32_t addr, uint32_t r0, uint32_t r1, uint32_t r2, uint32_t r3) {
    asm volatile("stmatrix.sync.aligned.m8n8.x4.shared.b16 [%0], {%1, %2, %3, %4};" ::"r"(addr), "r"(r0), "r"(r1), "r"(r2), "r"(r3) : "memory");
}
__device__ __forceinline__ uint32_t lds32(uint32_t a) { uint32_t v; asm volatile("ld.shared.b32 %0, [%1];" : "=r"(v) : "r"(a)); return v; }
__device__ __forceinline__ uint4 lds128(uint32_t a) { uint4 v; asm volatile("ld.shared.v4.b32 {%0,%1,%2,%3}, [%4];" : "=r"(v.x), "=r"(v.y), "=r"(v.z), "=r"(v.w) : "r"(a)); return v; }
__device__ __forceinline__ uint2 lds64(uint32_t a) { uint2 v; asm volatile("ld.shared.v2.b32 {%0,%1}, [%2];" : "=r"(v.x), "=r"(v.y) : "r"(a)); return v; }
__device__ __forceinline__ void sts128(uint32_t a, uint4 v) { asm volatile("st.shared.v4.b32 [%0], {%1,%2,%3,%4};" ::"r"(a), "r"(v.x), "r"(v.y), "r"(v.z), "r"(v.w) : "memory"); }
__device__ __forceinline__ uint32_t pack_bf16(float lo, float hi) { __nv_bfloat162 t = __floats2bfloat162_rn(lo, hi); return *reinterpret_cast<uint32_t*>(&t); }
__device__ __forceinline__ float bf16r(float v) { return __bfloat162float(__float2bfloat16_rn(v)); }
__device__ __forceinline__ float div_nr(float a, float d, float rd) { float q = a * rd; float r = fmaf(-q, d, a); return fmaf(r, rd, q); }
__device__ __forceinline__ float bf_lo(uint32_t v) { return __uint_as_float(v << 16); }
__device__ __forceinline__ float bf_hi(uint32_t v) { return __uint_as_float(v & 0xffff0000u); }

__device__ __forceinline__ void wgmma_rs_n64(float* d, uint32_t a0, uint32_t a1, uint32_t a2, uint32_t a3, uint64_t db, int sd) {
  asm volatile("{\n.reg .pred p;\nsetp.ne.b32 p, %37, 0;\n"
    "wgmma.mma_async.sync.aligned.m64n64k16.f32.bf16.bf16 {%0, %1, %2, %3, %4, %5, %6, %7, %8, %9, %10, %11, %12, %13, %14, %15, %16, %17, %18, %19, %20, %21, %22, %23, %24, %25, %26, %27, %28, %29, %30, %31}, {%32, %33, %34, %35}, %36, p, 1, 1, 0;\n}\n"
    : "+f"(d[0]), "+f"(d[1]), "+f"(d[2]), "+f"(d[3]), "+f"(d[4]), "+f"(d[5]), "+f"(d[6]), "+f"(d[7]), "+f"(d[8]), "+f"(d[9]), "+f"(d[10]), "+f"(d[11]), "+f"(d[12]), "+f"(d[13]), "+f"(d[14]), "+f"(d[15]), "+f"(d[16]), "+f"(d[17]), "+f"(d[18]), "+f"(d[19]), "+f"(d[20]), "+f"(d[21]), "+f"(d[22]), "+f"(d[23]), "+f"(d[24]), "+f"(d[25]), "+f"(d[26]), "+f"(d[27]), "+f"(d[28]), "+f"(d[29]), "+f"(d[30]), "+f"(d[31])
    : "r"(a0), "r"(a1), "r"(a2), "r"(a3), "l"(db), "r"(sd));
}
__device__ __forceinline__ void wgmma_ss_tb_n192(float* d, uint64_t da, uint64_t db, int sd) {
  asm volatile("{\n.reg .pred p;\nsetp.ne.b32 p, %98, 0;\n"
    "wgmma.mma_async.sync.aligned.m64n192k16.f32.bf16.bf16 {%0, %1, %2, %3, %4, %5, %6, %7, %8, %9, %10, %11, %12, %13, %14, %15, %16, %17, %18, %19, %20, %21, %22, %23, %24, %25, %26, %27, %28, %29, %30, %31, %32, %33, %34, %35, %36, %37, %38, %39, %40, %41, %42, %43, %44, %45, %46, %47, %48, %49, %50, %51, %52, %53, %54, %55, %56, %57, %58, %59, %60, %61, %62, %63, %64, %65, %66, %67, %68, %69, %70, %71, %72, %73, %74, %75, %76, %77, %78, %79, %80, %81, %82, %83, %84, %85, %86, %87, %88, %89, %90, %91, %92, %93, %94, %95}, %96, %97, p, 1, 1, 0, 1;\n}\n"
    : "+f"(d[0]), "+f"(d[1]), "+f"(d[2]), "+f"(d[3]), "+f"(d[4]), "+f"(d[5]), "+f"(d[6]), "+f"(d[7]), "+f"(d[8]), "+f"(d[9]), "+f"(d[10]), "+f"(d[11]), "+f"(d[12]), "+f"(d[13]), "+f"(d[14]), "+f"(d[15]), "+f"(d[16]), "+f"(d[17]), "+f"(d[18]), "+f"(d[19]), "+f"(d[20]), "+f"(d[21]), "+f"(d[22]), "+f"(d[23]), "+f"(d[24]), "+f"(d[25]), "+f"(d[26]), "+f"(d[27]), "+f"(d[28]), "+f"(d[29]), "+f"(d[30]), "+f"(d[31]), "+f"(d[32]), "+f"(d[33]), "+f"(d[34]), "+f"(d[35]), "+f"(d[36]), "+f"(d[37]), "+f"(d[38]), "+f"(d[39]), "+f"(d[40]), "+f"(d[41]), "+f"(d[42]), "+f"(d[43]), "+f"(d[44]), "+f"(d[45]), "+f"(d[46]), "+f"(d[47]), "+f"(d[48]), "+f"(d[49]), "+f"(d[50]), "+f"(d[51]), "+f"(d[52]), "+f"(d[53]), "+f"(d[54]), "+f"(d[55]), "+f"(d[56]), "+f"(d[57]), "+f"(d[58]), "+f"(d[59]), "+f"(d[60]), "+f"(d[61]), "+f"(d[62]), "+f"(d[63]), "+f"(d[64]), "+f"(d[65]), "+f"(d[66]), "+f"(d[67]), "+f"(d[68]), "+f"(d[69]), "+f"(d[70]), "+f"(d[71]), "+f"(d[72]), "+f"(d[73]), "+f"(d[74]), "+f"(d[75]), "+f"(d[76]), "+f"(d[77]), "+f"(d[78]), "+f"(d[79]), "+f"(d[80]), "+f"(d[81]), "+f"(d[82]), "+f"(d[83]), "+f"(d[84]), "+f"(d[85]), "+f"(d[86]), "+f"(d[87]), "+f"(d[88]), "+f"(d[89]), "+f"(d[90]), "+f"(d[91]), "+f"(d[92]), "+f"(d[93]), "+f"(d[94]), "+f"(d[95])
    : "l"(da), "l"(db), "r"(sd));
}
__device__ __forceinline__ void wgmma_ss_tb_n160(float* d, uint64_t da, uint64_t db, int sd) {
  asm volatile("{\n.reg .pred p;\nsetp.ne.b32 p, %82, 0;\n"
    "wgmma.mma_async.sync.aligned.m64n160k16.f32.bf16.bf16 {%0, %1, %2, %3, %4, %5, %6, %7, %8, %9, %10, %11, %12, %13, %14, %15, %16, %17, %18, %19, %20, %21, %22, %23, %24, %25, %26, %27, %28, %29, %30, %31, %32, %33, %34, %35, %36, %37, %38, %39, %40, %41, %42, %43, %44, %45, %46, %47, %48, %49, %50, %51, %52, %53, %54, %55, %56, %57, %58, %59, %60, %61, %62, %63, %64, %65, %66, %67, %68, %69, %70, %71, %72, %73, %74, %75, %76, %77, %78, %79}, %80, %81, p, 1, 1, 0, 1;\n}\n"
    : "+f"(d[0]), "+f"(d[1]), "+f"(d[2]), "+f"(d[3]), "+f"(d[4]), "+f"(d[5]), "+f"(d[6]), "+f"(d[7]), "+f"(d[8]), "+f"(d[9]), "+f"(d[10]), "+f"(d[11]), "+f"(d[12]), "+f"(d[13]), "+f"(d[14]), "+f"(d[15]), "+f"(d[16]), "+f"(d[17]), "+f"(d[18]), "+f"(d[19]), "+f"(d[20]), "+f"(d[21]), "+f"(d[22]), "+f"(d[23]), "+f"(d[24]), "+f"(d[25]), "+f"(d[26]), "+f"(d[27]), "+f"(d[28]), "+f"(d[29]), "+f"(d[30]), "+f"(d[31]), "+f"(d[32]), "+f"(d[33]), "+f"(d[34]), "+f"(d[35]), "+f"(d[36]), "+f"(d[37]), "+f"(d[38]), "+f"(d[39]), "+f"(d[40]), "+f"(d[41]), "+f"(d[42]), "+f"(d[43]), "+f"(d[44]), "+f"(d[45]), "+f"(d[46]), "+f"(d[47]), "+f"(d[48]), "+f"(d[49]), "+f"(d[50]), "+f"(d[51]), "+f"(d[52]), "+f"(d[53]), "+f"(d[54]), "+f"(d[55]), "+f"(d[56]), "+f"(d[57]), "+f"(d[58]), "+f"(d[59]), "+f"(d[60]), "+f"(d[61]), "+f"(d[62]), "+f"(d[63]), "+f"(d[64]), "+f"(d[65]), "+f"(d[66]), "+f"(d[67]), "+f"(d[68]), "+f"(d[69]), "+f"(d[70]), "+f"(d[71]), "+f"(d[72]), "+f"(d[73]), "+f"(d[74]), "+f"(d[75]), "+f"(d[76]), "+f"(d[77]), "+f"(d[78]), "+f"(d[79])
    : "l"(da), "l"(db), "r"(sd));
}
#define CONV_MMA_CHAIN(acc, A, db) \
  wgmma_rs_n64((acc) + 0, (A)[0], (A)[1], (A)[2], (A)[3], (db) + (0), 0); \
  wgmma_rs_n64((acc) + 32, (A)[0], (A)[1], (A)[2], (A)[3], (db) + (64), 0); \
  wgmma_rs_n64((acc) + 64, (A)[0], (A)[1], (A)[2], (A)[3], (db) + (128), 0); \
  wgmma_rs_n64((acc) + 96, (A)[0], (A)[1], (A)[2], (A)[3], (db) + (192), 0); \
  wgmma_rs_n64((acc) + 0, (A)[4], (A)[5], (A)[6], (A)[7], (db) + (-16), 1); \
  wgmma_rs_n64((acc) + 32, (A)[4], (A)[5], (A)[6], (A)[7], (db) + (48), 1); \
  wgmma_rs_n64((acc) + 64, (A)[4], (A)[5], (A)[6], (A)[7], (db) + (112), 1); \
  wgmma_rs_n64((acc) + 96, (A)[4], (A)[5], (A)[6], (A)[7], (db) + (176), 1); \
  wgmma_rs_n64((acc) + 0, (A)[8], (A)[9], (A)[10], (A)[11], (db) + (-32), 1); \
  wgmma_rs_n64((acc) + 32, (A)[8], (A)[9], (A)[10], (A)[11], (db) + (32), 1); \
  wgmma_rs_n64((acc) + 64, (A)[8], (A)[9], (A)[10], (A)[11], (db) + (96), 1); \
  wgmma_rs_n64((acc) + 96, (A)[8], (A)[9], (A)[10], (A)[11], (db) + (160), 1); \
  wgmma_rs_n64((acc) + 0, (A)[12], (A)[13], (A)[14], (A)[15], (db) + (-48), 1); \
  wgmma_rs_n64((acc) + 32, (A)[12], (A)[13], (A)[14], (A)[15], (db) + (16), 1); \
  wgmma_rs_n64((acc) + 64, (A)[12], (A)[13], (A)[14], (A)[15], (db) + (80), 1); \
  wgmma_rs_n64((acc) + 96, (A)[12], (A)[13], (A)[14], (A)[15], (db) + (144), 1); \
  wgmma_rs_n64((acc) + 32, (A)[16], (A)[17], (A)[18], (A)[19], (db) + (0), 1); \
  wgmma_rs_n64((acc) + 64, (A)[16], (A)[17], (A)[18], (A)[19], (db) + (64), 1); \
  wgmma_rs_n64((acc) + 96, (A)[16], (A)[17], (A)[18], (A)[19], (db) + (128), 1); \
  wgmma_rs_n64((acc) + 32, (A)[20], (A)[21], (A)[22], (A)[23], (db) + (-16), 1); \
  wgmma_rs_n64((acc) + 64, (A)[20], (A)[21], (A)[22], (A)[23], (db) + (48), 1); \
  wgmma_rs_n64((acc) + 96, (A)[20], (A)[21], (A)[22], (A)[23], (db) + (112), 1); \
  wgmma_rs_n64((acc) + 32, (A)[24], (A)[25], (A)[26], (A)[27], (db) + (-32), 1); \
  wgmma_rs_n64((acc) + 64, (A)[24], (A)[25], (A)[26], (A)[27], (db) + (32), 1); \
  wgmma_rs_n64((acc) + 96, (A)[24], (A)[25], (A)[26], (A)[27], (db) + (96), 1); \
  wgmma_rs_n64((acc) + 32, (A)[28], (A)[29], (A)[30], (A)[31], (db) + (-48), 1); \
  wgmma_rs_n64((acc) + 64, (A)[28], (A)[29], (A)[30], (A)[31], (db) + (16), 1); \
  wgmma_rs_n64((acc) + 96, (A)[28], (A)[29], (A)[30], (A)[31], (db) + (80), 1); \
  wgmma_rs_n64((acc) + 64, (A)[32], (A)[33], (A)[34], (A)[35], (db) + (0), 1); \
  wgmma_rs_n64((acc) + 96, (A)[32], (A)[33], (A)[34], (A)[35], (db) + (64), 1); \
  wgmma_rs_n64((acc) + 64, (A)[36], (A)[37], (A)[38], (A)[39], (db) + (-16), 1); \
  wgmma_rs_n64((acc) + 96, (A)[36], (A)[37], (A)[38], (A)[39], (db) + (48), 1); \
  wgmma_rs_n64((acc) + 64, (A)[40], (A)[41], (A)[42], (A)[43], (db) + (-32), 1); \
  wgmma_rs_n64((acc) + 96, (A)[40], (A)[41], (A)[42], (A)[43], (db) + (32), 1); \
  wgmma_rs_n64((acc) + 64, (A)[44], (A)[45], (A)[46], (A)[47], (db) + (-48), 1); \
  wgmma_rs_n64((acc) + 96, (A)[44], (A)[45], (A)[46], (A)[47], (db) + (16), 1); \
  wgmma_rs_n64((acc) + 96, (A)[48], (A)[49], (A)[50], (A)[51], (db) + (0), 1); \
  wgmma_rs_n64((acc) + 96, (A)[52], (A)[53], (A)[54], (A)[55], (db) + (-16), 1); \
  wgmma_rs_n64((acc) + 96, (A)[56], (A)[57], (A)[58], (A)[59], (db) + (-32), 1); \
  wgmma_rs_n64((acc) + 96, (A)[60], (A)[61], (A)[62], (A)[63], (db) + (-48), 1);
#define CONV_CHAIN_WG0(acc, A, db) \
  wgmma_rs_n64((acc) + 0, (A)[0], (A)[1], (A)[2], (A)[3], (db) + (0), 0); \
  wgmma_rs_n64((acc) + 32, (A)[0], (A)[1], (A)[2], (A)[3], (db) + (192), 0); \
  wgmma_rs_n64((acc) + 0, (A)[4], (A)[5], (A)[6], (A)[7], (db) + (-16), 1); \
  wgmma_rs_n64((acc) + 32, (A)[4], (A)[5], (A)[6], (A)[7], (db) + (176), 1); \
  wgmma_rs_n64((acc) + 0, (A)[8], (A)[9], (A)[10], (A)[11], (db) + (-32), 1); \
  wgmma_rs_n64((acc) + 32, (A)[8], (A)[9], (A)[10], (A)[11], (db) + (160), 1); \
  wgmma_rs_n64((acc) + 0, (A)[12], (A)[13], (A)[14], (A)[15], (db) + (-48), 1); \
  wgmma_rs_n64((acc) + 32, (A)[12], (A)[13], (A)[14], (A)[15], (db) + (144), 1); \
  wgmma_rs_n64((acc) + 32, (A)[16], (A)[17], (A)[18], (A)[19], (db) + (128), 1); \
  wgmma_rs_n64((acc) + 32, (A)[20], (A)[21], (A)[22], (A)[23], (db) + (112), 1); \
  wgmma_rs_n64((acc) + 32, (A)[24], (A)[25], (A)[26], (A)[27], (db) + (96), 1); \
  wgmma_rs_n64((acc) + 32, (A)[28], (A)[29], (A)[30], (A)[31], (db) + (80), 1); \
  wgmma_rs_n64((acc) + 32, (A)[32], (A)[33], (A)[34], (A)[35], (db) + (64), 1); \
  wgmma_rs_n64((acc) + 32, (A)[36], (A)[37], (A)[38], (A)[39], (db) + (48), 1); \
  wgmma_rs_n64((acc) + 32, (A)[40], (A)[41], (A)[42], (A)[43], (db) + (32), 1); \
  wgmma_rs_n64((acc) + 32, (A)[44], (A)[45], (A)[46], (A)[47], (db) + (16), 1); \
  wgmma_rs_n64((acc) + 32, (A)[48], (A)[49], (A)[50], (A)[51], (db) + (0), 1); \
  wgmma_rs_n64((acc) + 32, (A)[52], (A)[53], (A)[54], (A)[55], (db) + (-16), 1); \
  wgmma_rs_n64((acc) + 32, (A)[56], (A)[57], (A)[58], (A)[59], (db) + (-32), 1); \
  wgmma_rs_n64((acc) + 32, (A)[60], (A)[61], (A)[62], (A)[63], (db) + (-48), 1);
#define CONV_CHAIN_WG1(acc, A, db) \
  wgmma_rs_n64((acc) + 0, (A)[0], (A)[1], (A)[2], (A)[3], (db) + (64), 0); \
  wgmma_rs_n64((acc) + 32, (A)[0], (A)[1], (A)[2], (A)[3], (db) + (128), 0); \
  wgmma_rs_n64((acc) + 0, (A)[4], (A)[5], (A)[6], (A)[7], (db) + (48), 1); \
  wgmma_rs_n64((acc) + 32, (A)[4], (A)[5], (A)[6], (A)[7], (db) + (112), 1); \
  wgmma_rs_n64((acc) + 0, (A)[8], (A)[9], (A)[10], (A)[11], (db) + (32), 1); \
  wgmma_rs_n64((acc) + 32, (A)[8], (A)[9], (A)[10], (A)[11], (db) + (96), 1); \
  wgmma_rs_n64((acc) + 0, (A)[12], (A)[13], (A)[14], (A)[15], (db) + (16), 1); \
  wgmma_rs_n64((acc) + 32, (A)[12], (A)[13], (A)[14], (A)[15], (db) + (80), 1); \
  wgmma_rs_n64((acc) + 0, (A)[16], (A)[17], (A)[18], (A)[19], (db) + (0), 1); \
  wgmma_rs_n64((acc) + 32, (A)[16], (A)[17], (A)[18], (A)[19], (db) + (64), 1); \
  wgmma_rs_n64((acc) + 0, (A)[20], (A)[21], (A)[22], (A)[23], (db) + (-16), 1); \
  wgmma_rs_n64((acc) + 32, (A)[20], (A)[21], (A)[22], (A)[23], (db) + (48), 1); \
  wgmma_rs_n64((acc) + 0, (A)[24], (A)[25], (A)[26], (A)[27], (db) + (-32), 1); \
  wgmma_rs_n64((acc) + 32, (A)[24], (A)[25], (A)[26], (A)[27], (db) + (32), 1); \
  wgmma_rs_n64((acc) + 0, (A)[28], (A)[29], (A)[30], (A)[31], (db) + (-48), 1); \
  wgmma_rs_n64((acc) + 32, (A)[28], (A)[29], (A)[30], (A)[31], (db) + (16), 1); \
  wgmma_rs_n64((acc) + 32, (A)[32], (A)[33], (A)[34], (A)[35], (db) + (0), 1); \
  wgmma_rs_n64((acc) + 32, (A)[36], (A)[37], (A)[38], (A)[39], (db) + (-16), 1); \
  wgmma_rs_n64((acc) + 32, (A)[40], (A)[41], (A)[42], (A)[43], (db) + (-32), 1); \
  wgmma_rs_n64((acc) + 32, (A)[44], (A)[45], (A)[46], (A)[47], (db) + (-48), 1);

struct KParams {
    const __nv_bfloat16 *x, *k, *v, *shift_k, *ssm_k, *ssm_D, *w1, *w2;
    __nv_bfloat16* out;
};

__device__ __forceinline__ void bar_arrive(int id, int n) { asm volatile("bar.arrive %0, %1;" ::"r"(id), "r"(n) : "memory"); }

__global__ void __launch_bounds__(NTHREADS, 1)
fused_kernel(const __grid_constant__ CUtensorMap tm_xn, const __grid_constant__ CUtensorMap tm_w1,
             const __grid_constant__ CUtensorMap tm_h, const __grid_constant__ CUtensorMap tm_w2,
             const __grid_constant__ CUtensorMap tm_y2T, const __grid_constant__ CUtensorMap tm_xe,
             const __grid_constant__ CUtensorMap tm_xne, const __grid_constant__ CUtensorMap tm_uT, const __grid_constant__ CUtensorMap tm_out, const KParams P) {
    extern __shared__ __align__(1024) uint8_t smem[];
    const uint32_t sb = smem_u32(smem);
    const uint32_t bars = sb + OFF_BAR;
    const int tid = threadIdx.x, lane = tid & 31, warp = tid >> 5, wg = tid >> 7;
    const int cta = blockIdx.x;
    const int rb = cta >> 3;
    const int jn = cta & 7;
    const int kh = cta & 1;
    const int cb = (cta >> 1) & 3;
    const int ct = tid - 128;
    const int cw = ct >> 5;

    uint2 xv[2][5];
    uint4 wa = make_uint4(0,0,0,0), wb = make_uint4(0,0,0,0);
    if (wg != 0) {
        #pragma unroll
        for (int rr = 0; rr < 2; rr++) {
            const uint2* xr = reinterpret_cast<const uint2*>(P.x + (size_t)(cta * 16 + cw * 2 + rr) * D_);
            #pragma unroll
            for (int q = 0; q < 5; q++) xv[rr][q] = __ldg(xr + q * 32 + lane);
        }
        if (ct < 160) {
            wa = __ldg(reinterpret_cast<const uint4*>(P.shift_k + ct * 16));
            wb = __ldg(reinterpret_cast<const uint4*>(P.shift_k + ct * 16 + 8));
        }
    }

    if (tid == 0) {
        for (int i = 0; i < 4; i++) { mbar_init(bars + 8 * (B_FULL + i), 1); mbar_init(bars + 8 * (B_EMPTY + i), 8); }
        mbar_init(bars + 8 * B_HFULL, 1); mbar_init(bars + 8 * B_UFULL, 1);
        mbar_init(bars + 8 * B_XFREE, 8); mbar_init(bars + 8 * B_XFULL, 8); mbar_init(bars + 8 * B_YFULL, 1);
        mbar_init(bars + 8 * B_HST, 8); mbar_init(bars + 8 * B_STGFREE, 1);
        mbar_init(bars + 8 * B_KVFULL, 1); mbar_init(bars + 8 * B_KVFREE, 6); mbar_init(bars + 8 * B_USIG, 5); mbar_init(bars + 8 * B_YSIG, 8);
        asm volatile("fence.mbarrier_init.release.cluster;" ::: "memory");
    }
    unsigned epoch; asm volatile("ld.relaxed.gpu.global.u32 %0, [%1];" : "=r"(epoch) : "l"(&g_flags[FL_EPOCH]) : "memory");
    const unsigned ep1 = epoch + 1;
    __syncthreads();
    asm volatile("barrier.cluster.arrive.relaxed.aligned;" ::: "memory");

    if (wg == 0) {
        reg_dealloc<40>();
        if (warp == 0) {
            int it = 0;
            if (lane == 0) {
                for (int kb = 0; kb < 4; kb++) {
                    uint32_t st = sb + kb * STAGE_BYTES;
                    mbar_expect_tx(bars + 8 * (B_FULL + kb), 16384 + 24576);
                    for (int q = 0; q < 3; q++) tma_load_2d(st + 16384 + q * 8192, &tm_w1, bars + 8 * (B_FULL + kb), jn * 192 + q * 64, kb * 64);
                }
                const int r0 = cta ? cta * 16 - 3 : 0, nr = cta ? 19 : 16;
                bulk_prefetch_l2(reinterpret_cast<const uint8_t*>(P.w1) + (size_t)cta * 15360, 15360);
                bulk_prefetch_l2(P.k + (size_t)r0 * D_, nr * 1280);
                bulk_prefetch_l2(P.v + (size_t)cta * 16 * D_, 16 * 1280);
                flag_wait(&g_flags[FL_XN + rb], 8u * ep1);
                fence_proxy_async();
                for (int kb = 0; kb < 4; kb++) tma_load_2d(sb + kb * STAGE_BYTES, &tm_xn, bars + 8 * (B_FULL + kb), kb * 64, rb * 128);
                mbar_expect_tx(bars + 8 * B_KVFULL, (nr + 16) * 1280);
                bulk_load(sb + OFF_KST + (19 - nr) * 1280, P.k + (size_t)r0 * D_, nr * 1280, bars + 8 * B_KVFULL);
                bulk_load(sb + OFF_VST, P.v + (size_t)cta * 16 * D_, 16 * 1280, bars + 8 * B_KVFULL);
                bulk_prefetch_l2(P.ssm_k + (size_t)cta * 5 * S_, 5 * 4096);
                bulk_prefetch_l2(reinterpret_cast<const uint8_t*>(P.w2) + (size_t)cta * 15360, 15360);
                it = 4;
                for (int kb = 4; kb < 10; kb++, it++) {
                    int s = it & 3;
                    mbar_wait(bars + 8 * (B_EMPTY + s), ((it >> 2) - 1) & 1);
                    uint32_t st = sb + s * STAGE_BYTES;
                    mbar_expect_tx(bars + 8 * (B_FULL + s), 16384 + 24576);
                    for (int q = 0; q < 3; q++) tma_load_2d(st + 16384 + q * 8192, &tm_w1, bars + 8 * (B_FULL + s), jn * 192 + q * 64, kb * 64);
                    tma_load_2d(st, &tm_xn, bars + 8 * (B_FULL + s), kb * 64, rb * 128);
                }
            }
            __syncwarp();
            mbar_wait(bars + 8 * B_KVFREE, 0);
            for (int i = lane; i < 280; i += 32) sts128(sb + OFF_U + (i / 56) * U_PITCH + (i % 56) * 16, make_uint4(0, 0, 0, 0));
            if (lane < 10) sts128(sb + OFF_HC + (lane >> 1) * HC_PITCH + (lane & 1) * HC1_OFF, make_uint4(0, 0, 0, 0));
            fence_proxy_async_smem();
            __syncwarp();
            if (lane == 0) {
                mbar_expect_tx(bars + 8 * B_HFULL, 5 * 4096);
                for (int ch = 0; ch < 5; ch++)
                    bulk_load(sb + OFF_HC + ch * HC_PITCH + 16, P.ssm_k + (size_t)(cta * 5 + ch) * S_, 4096, bars + 8 * B_HFULL);
                flag_wait(&g_flags[FL_U], (unsigned)NCTA * ep1);
                fence_proxy_async();
                mbar_expect_tx(bars + 8 * B_UFULL, 5 * 4096);
                for (int ch = 0; ch < 5; ch++)
                    bulk_load(sb + OFF_U + ch * U_PITCH + U_ZPAD, g_uT + (size_t)(cta * 5 + ch) * S_, 4096, bars + 8 * B_UFULL);
            }
            __syncwarp();
            if (lane < 4) flag_wait(&g_flags[FL_H + rb * 8 + kh * 4 + lane], ep1);
            __syncwarp();
            if (lane == 0) {
                fence_proxy_async();
                it = 10;
                for (int kb = 0; kb < 12; kb++, it++) {
                    int s = it & 3;
                    mbar_wait(bars + 8 * (B_EMPTY + s), ((it >> 2) - 1) & 1);
                    uint32_t st = sb + s * STAGE_BYTES;
                    mbar_expect_tx(bars + 8 * (B_FULL + s), 16384 + 20480);
                    for (int q = 0; q < 5; q++) tma_load_2d(st + 16384 + q * 4096, &tm_w2, bars + 8 * (B_FULL + s), cb * 160 + q * 32, kh * 768 + kb * 64);
                    tma_load_2d(st, &tm_h, bars + 8 * (B_FULL + s), kh * 768 + kb * 64, rb * 128);
                }
                {
                    int s = it & 3;
                    mbar_wait(bars + 8 * (B_EMPTY + s), ((it >> 2) - 1) & 1);
                    uint32_t st = sb + s * STAGE_BYTES;
                    mbar_expect_tx(bars + 8 * (B_FULL + s), 2 * 20480);
                    tma_load_2d(st, &tm_xe, bars + 8 * (B_FULL + s), cb * 160 + kh * 80, rb * 128);
                    tma_load_2d(st + 20480, &tm_xne, bars + 8 * (B_FULL + s), cb * 160 + kh * 80, rb * 128);
                }
            }
            __syncwarp();
            if (lane < 16) flag_wait(&g_flags[FL_Y + cb * 32 + kh * 16 + lane], ep1);
            __syncwarp();
            if (lane == 0) {
                fence_proxy_async();
                mbar_expect_tx(bars + 8 * B_YFULL, 20480);
                for (int q = 0; q < 2; q++) tma_load_2d(sb + OFF_YT + q * 10240, &tm_y2T, bars + 8 * B_YFULL, rb * 128 + q * 64, cb * 160 + kh * 80);
            }
            __syncwarp();
        } else if (warp == 1) {
            if (lane == 0) {
                mbar_wait(bars + 8 * B_HST, 0);
                for (int q = 0; q < 3; q++) tma_store_2d(&tm_h, sb + q * 16384, jn * 192 + q * 64, rb * 128);
                bulk_commit();
                bulk_wait0();
                mbar_arrive(bars + 8 * B_STGFREE);
                __threadfence();
                st_release(&g_flags[FL_H + cta], ep1);
            }
            __syncwarp();
        } else if (warp == 2) {
            if (lane == 0) {
                mbar_wait(bars + 8 * B_USIG, 0);
                for (int q = 0; q < 5; q++) tma_store_2d(&tm_uT, sb + OFF_UST + q * 4096, cta * 16, q * 128);
                bulk_commit();
                asm volatile("cp.async.bulk.wait_group.read 0;" ::: "memory");
                mbar_arrive(bars + 8 * B_KVFREE);
                bulk_wait0();
                __threadfence();
                red_release_add(&g_flags[FL_U], 1u);
            }
            __syncwarp();
        } else {
            if (lane == 0) {
                mbar_wait(bars + 8 * B_YSIG, 0);
                red_release_add(&g_flags[FL_Y + cta], 1u);
            }
            __syncwarp();
        }
    } else {
        reg_alloc<232>();
        const int wgc = __shfl_sync(0xffffffffu, wg - 1, 0);
        const int w4 = cw & 3;
        const int g4 = lane >> 2, c4 = lane & 3;
        TICK(0);

        {
            #pragma unroll 1
            for (int rr = 0; rr < 2; rr++) {
                float f[20];
                #pragma unroll
                for (int q = 0; q < 5; q++) { uint2 w = rr ? xv[1][q] : xv[0][q]; f[4*q] = bf_lo(w.x); f[4*q+1] = bf_hi(w.x); f[4*q+2] = bf_lo(w.y); f[4*q+3] = bf_hi(w.y); }
                float s0 = 0.f, s1 = 0.f, s2 = 0.f, s3 = 0.f;
                #pragma unroll
                for (int q = 0; q < 5; q++) { s0 += f[4*q]; s1 += f[4*q+1]; s2 += f[4*q+2]; s3 += f[4*q+3]; }
                float mean = (s0 + s1) + (s2 + s3);
                #pragma unroll
                for (int o = 16; o; o >>= 1) mean += __shfl_xor_sync(0xffffffffu, mean, o);
                mean *= (1.0f / 640.0f);
                s0 = 0.f; s1 = 0.f; s2 = 0.f; s3 = 0.f;
                #pragma unroll
                for (int q = 0; q < 5; q++) {
                    float d0 = f[4*q] - mean, d1 = f[4*q+1] - mean, d2 = f[4*q+2] - mean, d3 = f[4*q+3] - mean;
                    s0 = fmaf(d0, d0, s0); s1 = fmaf(d1, d1, s1); s2 = fmaf(d2, d2, s2); s3 = fmaf(d3, d3, s3);
                }
                float vs = (s0 + s1) + (s2 + s3);
                #pragma unroll
                for (int o = 16; o; o >>= 1) vs += __shfl_xor_sync(0xffffffffu, vs, o);
                const float mb = bf16r(mean);
                const float vb = bf16r(vs * (1.0f / 640.0f));
                const float den = bf16r(sqrtf(bf16r(vb + 1e-5f)));
                const float rden = __frcp_rn(den);
                uint2* xo = reinterpret_cast<uint2*>(g_xn + (size_t)(cta * 16 + cw * 2 + rr) * D_);
                #pragma unroll
                for (int q = 0; q < 5; q++) {
                    float a0 = bf16r(f[4*q] - mb), a1 = bf16r(f[4*q+1] - mb), a2 = bf16r(f[4*q+2] - mb), a3 = bf16r(f[4*q+3] - mb);
                    uint2 o; o.x = pack_bf16(div_nr(a0, den, rden), div_nr(a1, den, rden)); o.y = pack_bf16(div_nr(a2, den, rden), div_nr(a3, den, rden));
                    xo[q * 32 + lane] = o;
                }
            }
            TICK(18);
            bar_sync(1, 256);
            if (ct == 255) red_release_add(&g_flags[FL_XN + rb], 1u);
            TICK(1);
        }
        TICK(3);
        int it = 0;
        {
            float acc[96];
            uint2 kk[19], vv[16];
            uint32_t wp[2][4];
            #pragma unroll 1
            for (int kb = 0; kb < 10; kb++, it++) {
                int s = it & 3;
                mbar_wait(bars + 8 * (B_FULL + s), (it >> 2) & 1);
                uint32_t st = sb + s * STAGE_BYTES;
                uint64_t da = make_desc(st + wgc * 8192, 16, 1024, 1);
                uint64_t db = make_desc(st + 16384, 8192, 1024, 1);
                if (kb == 0) TICK(4);
                wg_fence();
                #pragma unroll
                for (int k = 0; k < 4; k++) wgmma_ss_tb_n192(acc, da + k * 2, db + k * 128, (kb | k) ? 1 : 0);
                wg_commit();
                if (kb > 0) {
                    wg_wait<1>();
                    if (kb - 1 < 8 && lane == 0) mbar_arrive(bars + 8 * (B_EMPTY + ((it - 1) & 3)));
                }
                if ((kb == 4 || kb == 5) && ct < 160) {
                    const int p = kb - 4;
                    const int c0 = ct * 4;
                    const int t0 = cta * 16;
                    if (p == 0) {
                        mbar_wait(bars + 8 * B_KVFULL, 0);
                        TICK(29);
                        #pragma unroll
                        for (int i = 0; i < 19; i++) kk[i] = (cta > 0 || i >= 3) ? lds64(sb + OFF_KST + i * 1280 + ct * 8) : make_uint2(0, 0);
                        #pragma unroll
                        for (int i = 0; i < 16; i++) vv[i] = lds64(sb + OFF_VST + i * 1280 + ct * 8);
                        __syncwarp();
                        if (lane == 0) mbar_arrive(bars + 8 * B_KVFREE);
                        wp[0][0] = __byte_perm(wa.x, wa.z, 0x5410); wp[0][1] = __byte_perm(wa.x, wa.z, 0x7632);
                        wp[0][2] = __byte_perm(wa.y, wa.w, 0x5410); wp[0][3] = __byte_perm(wa.y, wa.w, 0x7632);
                        wp[1][0] = __byte_perm(wb.x, wb.z, 0x5410); wp[1][1] = __byte_perm(wb.x, wb.z, 0x7632);
                        wp[1][2] = __byte_perm(wb.y, wb.w, 0x5410); wp[1][3] = __byte_perm(wb.y, wb.w, 0x7632);
                    }
                    uint32_t u[16];
                    #pragma unroll
                    for (int i = 0; i < 16; i++) {
                        auto ld = [&](int idx) { uint32_t r = p ? kk[idx].y : kk[idx].x; return *reinterpret_cast<__nv_bfloat162*>(&r); };
                        auto wv = [&](int d) { return *reinterpret_cast<__nv_bfloat162*>(&wp[p][d]); };
                        __nv_bfloat162 a = __hmul2_rn(ld(i), wv(3));
                        a = __hadd2_rn(a, __hmul2_rn(ld(i + 1), wv(2)));
                        a = __hadd2_rn(a, __hmul2_rn(ld(i + 2), wv(1)));
                        a = __hadd2_rn(a, __hmul2_rn(ld(i + 3), wv(0)));
                        uint32_t vr = p ? vv[i].y : vv[i].x;
                        a = __hmul2_rn(a, *reinterpret_cast<__nv_bfloat162*>(&vr));
                        u[i] = *reinterpret_cast<uint32_t*>(&a);
                    }
                    uint4 ck[4];
                    #pragma unroll
                    for (int e = 0; e < 2; e++) {
                        const uint32_t sel = e ? 0x7632 : 0x5410;
                        #pragma unroll
                        for (int g = 0; g < 2; g++) {
                            ck[2*e+g].x = __byte_perm(u[8*g+7], u[8*g+6], sel);
                            ck[2*e+g].y = __byte_perm(u[8*g+5], u[8*g+4], sel);
                            ck[2*e+g].z = __byte_perm(u[8*g+3], u[8*g+2], sel);
                            ck[2*e+g].w = __byte_perm(u[8*g+1], u[8*g+0], sel);
                        }
                    }
                    #pragma unroll
                    for (int j = 0; j < 4; j++) {
                        const int jj = (j + lane) & 3;
                        uint4 o = (jj & 2) ? ((jj & 1) ? ck[3] : ck[2]) : ((jj & 1) ? ck[1] : ck[0]);
                        sts128(sb + OFF_UST + ct * 128 + p * 64 + jj * 16, o);
                    }
                    if (p == 1) fence_proxy_async_smem();
                    if (p == 1) { __syncwarp(); if (lane == 0) mbar_arrive(bars + 8 * B_USIG); }
                    TICK(30 + p);
                }
                if (kb == 5) TICK(2);
                if (kb == 8) {
                    mbar_wait(bars + 8 * B_HFULL, 0);
                    #pragma unroll
                    for (int ch = 0; ch < 5; ch++) {
                        uint32_t b0 = sb + OFF_HC + ch * HC_PITCH + 16;
                        uint4 a = lds128(b0 + ct * 16);
                        uint32_t nx = (ct < 255) ? lds32(b0 + ct * 16 + 16) : 0u;
                        uint4 o;
                        o.x = __byte_perm(a.x, a.y, 0x5432); o.y = __byte_perm(a.y, a.z, 0x5432); o.z = __byte_perm(a.z, a.w, 0x5432); o.w = __byte_perm(a.w, nx, 0x5432);
                        sts128(sb + OFF_HC + ch * HC_PITCH + HC1_OFF + 16 + ct * 16, o);
                        if (ct == 0) {
                            uint32_t h0 = a.x & 0xffffu;
                            asm volatile("st.shared.b32 [%0], %1;" ::"r"(sb + OFF_HC + ch * HC_PITCH + HC1_OFF + 12), "r"(h0 << 16) : "memory");
                        }
                    }
                }
            }
            wg_wait<0>();
            TICK(5);
            bar_sync(1, 256);
            #pragma unroll
            for (int j = 0; j < 24; j += 2) {
                uint32_t r0 = pack_bf16(fmaxf(acc[4*j], 0.f), fmaxf(acc[4*j+1], 0.f));
                uint32_t r1 = pack_bf16(fmaxf(acc[4*j+2], 0.f), fmaxf(acc[4*j+3], 0.f));
                uint32_t r2 = pack_bf16(fmaxf(acc[4*j+4], 0.f), fmaxf(acc[4*j+5], 0.f));
                uint32_t r3 = pack_bf16(fmaxf(acc[4*j+6], 0.f), fmaxf(acc[4*j+7], 0.f));
                int mat = lane >> 3;
                int row = wgc * 64 + w4 * 16 + (lane & 7) + (mat & 1) * 8;
                int colg = j + (mat >> 1);
                int box = colg >> 3, cc = colg & 7;
                uint32_t addr = sb + box * 16384 + row * 128 + ((cc ^ (row & 7)) << 4);
                stmatrix_x4(addr, r0, r1, r2, r3);
            }
            fence_proxy_async_smem();
            __syncwarp();
            if (lane == 0) mbar_arrive(bars + 8 * B_HST);
            TICK(6);
        }

        {
            bar_sync(1, 256);
            mbar_wait(bars + 8 * B_UFULL, 0);
            TICK(7);
            const uint32_t ps = sb + (wgc ? 0 : STAGE_BYTES);
            const int par = (g4 + 1) & 1;
            #pragma unroll 1
            for (int ch = wgc; ch < 5; ch += 2) {
                const uint32_t hbase = sb + OFF_HC + ch * HC_PITCH;
                const float Dc = __bfloat162float(__ldg(P.ssm_D + cta * 5 + ch));
                const uint32_t pb = hbase + (par ? (HC1_OFF + 16 - 2) : 16) + 2 * (16 * w4 + g4 - 7 + 2 * c4);
                uint32_t A[64];
                #pragma unroll
                for (int g2 = 0; g2 < 16; g2++) {
                    A[4*g2+0] = lds32(pb + 128 * (2*g2+1));
                    A[4*g2+1] = lds32(pb + 128 * (2*g2+1) + 16);
                    A[4*g2+2] = lds32(pb + 128 * (2*g2));
                    A[4*g2+3] = lds32(pb + 128 * (2*g2) + 16);
                }
                float acc[128];
                const uint64_t db = make_desc(sb + OFF_U + ch * U_PITCH + U_ZPAD - 128, 128, 128, 0);
                TICK(19 + 2 * ch);
                if (ch > 0) bar_sync(4 + wgc, 256);
                wg_fence();
                CONV_MMA_CHAIN(acc, A, db);
                wg_commit();
                if (ch < 4) bar_arrive(4 + (wgc ^ 1), 256);
                wg_wait<0>();
                TICK(20 + 2 * ch);
                if (ch < 2) {
                    mbar_wait(bars + 8 * B_STGFREE, 0);
                    if (lane == 0) mbar_arrive(bars + 8 * (B_EMPTY + wgc));
                }
                {
                    float got[32];
                    #pragma unroll
                    for (int j = 0; j < 32; j++) {
                        float send = (c4 == 3) ? (j ? acc[4*j-1] : 0.f) : acc[4*j+3];
                        got[j] = __shfl_sync(0xffffffffu, send, (lane & ~3) | ((c4 + 3) & 3));
                    }
                    const uint32_t dst = ps + ((w4 * 8 + g4) * 264 + 2 * w4 + 2 * c4) * 4;
                    #pragma unroll
                    for (int j = 0; j < 32; j++) {
                        float p0 = acc[4*j] + got[j], p1 = acc[4*j+1] + acc[4*j+2];
                        asm volatile("st.shared.v2.f32 [%0], {%1, %2};" ::"r"(dst + j * 32), "f"(p0), "f"(p1) : "memory");
                    }
                }
                if (ch == 0) TICK(21);
                bar_sync(2 + wgc, 128);
                if (ch == 0) TICK(22);
                const int t128 = ct & 127;
                uint4 o[2];
                #pragma unroll
                for (int hh = 0; hh < 2; hh++) {
                    int a = t128 + 128 * hh;
                    uint4 ub = lds128(sb + OFF_U + ch * U_PITCH + U_ZPAD + a * 16);
                    uint32_t uw[4] = {ub.x, ub.y, ub.z, ub.w};
                    float y2[8];
                    #pragma unroll
                    for (int b = 0; b < 8; b++) {
                        uint32_t ad = ps + (b * 264 + a) * 4;
                        float y = __uint_as_float(lds32(ad));
                        float y1 = __uint_as_float(lds32(ad + 8 * 264 * 4));
                        float y2_ = __uint_as_float(lds32(ad + 16 * 264 * 4));
                        float y3 = __uint_as_float(lds32(ad + 24 * 264 * 4));
                        if (hh == 0) { if (a < 2) y1 = 0.f; if (a < 4) y2_ = 0.f; if (a < 6) y3 = 0.f; }
                        float yy = (y + y1) + (y2_ + y3);
                        int e = 7 - b;
                        float uu = (e & 1) ? bf_hi(uw[e >> 1]) : bf_lo(uw[e >> 1]);
                        y2[b] = bf16r(bf16r(yy) + bf16r(uu * Dc));
                    }
                    o[hh].x = pack_bf16(y2[0], y2[1]); o[hh].y = pack_bf16(y2[2], y2[3]); o[hh].z = pack_bf16(y2[4], y2[5]); o[hh].w = pack_bf16(y2[6], y2[7]);
                }
                #pragma unroll
                for (int hh = 0; hh < 2; hh++) *reinterpret_cast<uint4*>(g_y2T + (size_t)(cta * 5 + ch) * S_ + 8 * (t128 + 128 * hh)) = o[hh];
                if (ch == 0) TICK(25);
                bar_sync(2 + wgc, 128);
                if (ch == 0) TICK(26);
            }
            __syncwarp();
            if (lane == 0) { mbar_arrive(bars + 8 * B_YSIG); mbar_arrive(bars + 8 * (B_EMPTY + (wgc ^ 1))); }
            TICK(8);
            asm volatile("barrier.cluster.wait.acquire.aligned;" ::: "memory");
            if (lane == 0) {
                uint32_t peer_bar;
                asm volatile("mapa.shared::cluster.u32 %0, %1, %2;" : "=r"(peer_bar) : "r"(bars + 8 * B_XFREE), "r"(kh ^ 1));
                mbar_arrive_remote(peer_bar);
            }
        }

        {
            float acc[80];
            for (int kb = 0; kb < 12; kb++, it++) {
                int s = it & 3;
                mbar_wait(bars + 8 * (B_FULL + s), (it >> 2) & 1);
                uint32_t st = sb + s * STAGE_BYTES;
                uint64_t da = make_desc(st + wgc * 8192, 16, 1024, 1);
                uint64_t db = make_desc(st + 16384, 4096, 512, 2);
                if (kb == 0) TICK(9);
                wg_fence();
                #pragma unroll
                for (int k = 0; k < 4; k++) wgmma_ss_tb_n160(acc, da + k * 2, db + k * 64, (kb | k) ? 1 : 0);
                wg_commit();
                if (kb > 0) {
                    wg_wait<1>();
                    if (lane == 0) mbar_arrive(bars + 8 * (B_EMPTY + ((it - 1) & 3)));
                }
            }
            wg_wait<0>();
            TICK(10);
            mbar_wait_cluster(bars + 8 * B_XFREE, 0);
            {
                uint32_t xb_peer, bar_peer;
                asm volatile("mapa.shared::cluster.u32 %0, %1, %2;" : "=r"(xb_peer) : "r"(sb + OFF_XB), "r"(kh ^ 1));
                asm volatile("mapa.shared::cluster.u32 %0, %1, %2;" : "=r"(bar_peer) : "r"(bars + 8 * B_XFULL), "r"(kh ^ 1));
                #pragma unroll
                for (int i = 0; i < 10; i++) {
                    float v0 = kh ? acc[4*i] : acc[40+4*i], v1 = kh ? acc[4*i+1] : acc[40+4*i+1], v2 = kh ? acc[4*i+2] : acc[40+4*i+2], v3 = kh ? acc[4*i+3] : acc[40+4*i+3];
                    asm volatile("st.shared::cluster.v4.f32 [%0], {%1,%2,%3,%4};" ::"r"(xb_peer + (i * 256 + ct) * 16), "f"(v0), "f"(v1), "f"(v2), "f"(v3) : "memory");
                }
                __syncwarp();
                if (lane == 0) mbar_arrive_remote(bar_peer);
            }
            const uint32_t ownb = sb + ((it + 1) & 3) * STAGE_BYTES;
            bar_sync(1, 256);
            #pragma unroll
            for (int i = 0; i < 10; i++) {
                float v0 = kh ? acc[40+4*i] : acc[4*i], v1 = kh ? acc[40+4*i+1] : acc[4*i+1], v2 = kh ? acc[40+4*i+2] : acc[4*i+2], v3 = kh ? acc[40+4*i+3] : acc[4*i+3];
                asm volatile("st.shared.v4.f32 [%0], {%1,%2,%3,%4};" ::"r"(ownb + (i * 256 + ct) * 16), "f"(v0), "f"(v1), "f"(v2), "f"(v3) : "memory");
            }
            const int col0 = cb * 160 + kh * 80;
            const uint32_t xt = sb + (it & 3) * STAGE_BYTES;
            mbar_wait(bars + 8 * (B_FULL + (it & 3)), (it >> 2) & 1);
            mbar_wait(bars + 8 * B_YFULL, 0);
            mbar_wait_cluster(bars + 8 * B_XFULL, 0);
            TICK(11);
            #pragma unroll 2
            for (int i = 0; i < 10; i++) {
                uint4 r = lds128(sb + OFF_XB + (i * 256 + ct) * 16);
                uint4 ro = lds128(ownb + (i * 256 + ct) * 16);
                float z[4];
                z[0] = __uint_as_float(ro.x) + __uint_as_float(r.x);
                z[1] = __uint_as_float(ro.y) + __uint_as_float(r.y);
                z[2] = __uint_as_float(ro.z) + __uint_as_float(r.z);
                z[3] = __uint_as_float(ro.w) + __uint_as_float(r.w);
                #pragma unroll
                for (int hf = 0; hf < 2; hf++) {
                    const int rl = wgc * 64 + w4 * 16 + g4 + hf * 8;
                    const int cl = 8 * i + 2 * c4;
                    const uint32_t xw = lds32(xt + rl * 160 + cl * 2);
                    const uint32_t xnw = lds32(xt + 20480 + rl * 160 + cl * 2);
                    const int box = rl >> 6, tl = rl & 63;
                    const uint32_t yb = sb + OFF_YT + box * 10240 + ((tl & 7) << 1);
                    uint32_t y0, y1;
                    asm volatile("ld.shared.u16 %0, [%1];" : "=r"(y0) : "r"(yb + cl * 128 + (((tl >> 3) ^ (cl & 7)) << 4)));
                    asm volatile("ld.shared.u16 %0, [%1];" : "=r"(y1) : "r"(yb + (cl + 1) * 128 + (((tl >> 3) ^ ((cl + 1) & 7)) << 4)));
                    const uint32_t yw = __byte_perm(y0, y1, 0x5410);
                    const uint32_t zw = pack_bf16(z[2 * hf], z[2 * hf + 1]);
                    const float z0 = bf_lo(zw), z1 = bf_hi(zw);
                    const uint32_t gw = pack_bf16(__fdividef(z0, 1.0f + __expf(-z0)), __fdividef(z1, 1.0f + __expf(-z1)));
                    __nv_bfloat162 sv = __hmul2_rn(*reinterpret_cast<const __nv_bfloat162*>(&xnw), *reinterpret_cast<const __nv_bfloat162*>(&yw));
                    sv = __hmul2_rn(sv, *reinterpret_cast<const __nv_bfloat162*>(&gw));
                    sv = __hadd2_rn(*reinterpret_cast<const __nv_bfloat162*>(&xw), sv);
                    asm volatile("st.shared.b32 [%0], %1;" ::"r"(xt + rl * 160 + cl * 2), "r"(*reinterpret_cast<uint32_t*>(&sv)) : "memory");
                }
            }
            fence_proxy_async_smem();
            bar_sync(1, 256);
            if (ct == 0) {
                tma_store_2d(&tm_out, xt, col0, rb * 128);
                bulk_commit();
                asm volatile("cp.async.bulk.wait_group.read 0;" ::: "memory");
            }
        }
    }
    if (wg == 0) asm volatile("barrier.cluster.wait.acquire.aligned;" ::: "memory");
    __syncthreads();
    if (tid == 0) {
        __threadfence();
        unsigned t = atomicAdd(&g_flags[FL_TICKET], 1u);
        if (t == NCTA - 1) { g_flags[FL_TICKET] = 0; __threadfence(); st_release(&g_flags[FL_EPOCH], ep1); }
    }
}

typedef CUresult (*EncFn)(CUtensorMap*, CUtensorMapDataType, cuuint32_t, void*, const cuuint64_t*, const cuuint64_t*, const cuuint32_t*, const cuuint32_t*,
                          CUtensorMapInterleave, CUtensorMapSwizzle, CUtensorMapL2promotion, CUtensorMapFloatOOBfill);

bool make_map_2d(EncFn enc, CUtensorMap* m, const void* ptr, uint64_t inner, uint64_t outer, uint32_t box_in, uint32_t box_out, CUtensorMapSwizzle swz) {
    cuuint64_t dims[2] = {inner, outer};
    cuuint64_t strides[1] = {inner * 2};
    cuuint32_t box[2] = {box_in, box_out};
    cuuint32_t es[2] = {1, 1};
    return enc(m, CU_TENSOR_MAP_DATA_TYPE_BFLOAT16, 2, const_cast<void*>(ptr), dims, strides, box, es, CU_TENSOR_MAP_INTERLEAVE_NONE, swz,
               CU_TENSOR_MAP_L2_PROMOTION_L2_128B, CU_TENSOR_MAP_FLOAT_OOB_FILL_NONE) == CUDA_SUCCESS;
}

}

extern "C" void kernel_launch(void* const* d_in, const int* in_sizes, int n_in, void* d_out, int out_size) {
    static EncFn enc = nullptr;
    if (!enc) {
        void* fn = nullptr; cudaDriverEntryPointQueryResult q;
        cudaGetDriverEntryPoint("cuTensorMapEncodeTiled", &fn, cudaEnableDefault, &q);
        enc = (EncFn)fn;
        cudaFuncSetAttribute(fused_kernel, cudaFuncAttributeMaxDynamicSharedMemorySize, SMEM_BYTES);
    }
    KParams P;
    P.x = (const __nv_bfloat16*)d_in[0]; P.k = (const __nv_bfloat16*)d_in[1]; P.v = (const __nv_bfloat16*)d_in[2];
    P.shift_k = (const __nv_bfloat16*)d_in[3]; P.ssm_k = (const __nv_bfloat16*)d_in[4]; P.ssm_D = (const __nv_bfloat16*)d_in[5];
    P.w1 = (const __nv_bfloat16*)d_in[7]; P.w2 = (const __nv_bfloat16*)d_in[8];
    P.out = (__nv_bfloat16*)d_out;
    void *p_xn, *p_h, *p_y2T;
    cudaGetSymbolAddress(&p_xn, g_xn); cudaGetSymbolAddress(&p_h, g_h); cudaGetSymbolAddress(&p_y2T, g_y2T);
    CUtensorMap tm_xn, tm_w1, tm_h, tm_w2, tm_y2T, tm_xe, tm_xne, tm_uT, tm_out;
    make_map_2d(enc, &tm_out, P.out, D_, S_, 80, 128, CU_TENSOR_MAP_SWIZZLE_NONE);
    void* p_uT; cudaGetSymbolAddress(&p_uT, g_uT);
    make_map_2d(enc, &tm_uT, p_uT, S_, D_, 16, 128, CU_TENSOR_MAP_SWIZZLE_NONE);
    make_map_2d(enc, &tm_xn, p_xn, D_, S_, 64, 128, CU_TENSOR_MAP_SWIZZLE_128B);
    make_map_2d(enc, &tm_w1, P.w1, DFF_, D_, 64, 64, CU_TENSOR_MAP_SWIZZLE_128B);
    make_map_2d(enc, &tm_h, p_h, DFF_, S_, 64, 128, CU_TENSOR_MAP_SWIZZLE_128B);
    make_map_2d(enc, &tm_w2, P.w2, D_, DFF_, 32, 64, CU_TENSOR_MAP_SWIZZLE_64B);
    make_map_2d(enc, &tm_y2T, p_y2T, S_, D_, 64, 80, CU_TENSOR_MAP_SWIZZLE_128B);
    make_map_2d(enc, &tm_xe, P.x, D_, S_, 80, 128, CU_TENSOR_MAP_SWIZZLE_NONE);
    make_map_2d(enc, &tm_xne, p_xn, D_, S_, 80, 128, CU_TENSOR_MAP_SWIZZLE_NONE);

    cudaLaunchConfig_t cfg = {};
    cfg.gridDim = dim3(NCTA); cfg.blockDim = dim3(NTHREADS); cfg.dynamicSmemBytes = SMEM_BYTES; cfg.stream = cudaStreamPerThread;
    cudaLaunchAttribute at[1];
    at[0].id = cudaLaunchAttributeClusterDimension; at[0].val.clusterDim.x = 2; at[0].val.clusterDim.y = 1; at[0].val.clusterDim.z = 1;
    cfg.attrs = at; cfg.numAttrs = 1;
    cudaLaunchKernelEx(&cfg, fused_kernel, tm_xn, tm_w1, tm_h, tm_w2, tm_y2T, tm_xe, tm_xne, tm_uT, tm_out, P);
}
```

```cpp
#include <cuda_runtime.h>
#include <cuda_bf16.h>
#include <cuda.h>
#include <stdint.h>

namespace {

constexpr int S_ = 2048, D_ = 640, DFF_ = 1536;
constexpr int NCTA = 128;
constexpr int NTHREADS = 384;

__device__ __align__(1024) __nv_bfloat16 g_xn[S_ * D_];
__device__ __align__(1024) __nv_bfloat16 g_uT[D_ * S_];
__device__ __align__(1024) __nv_bfloat16 g_h[S_ * DFF_];
__device__ __align__(1024) __nv_bfloat16 g_y2T[D_ * S_];
__device__ __align__(128) unsigned int g_flags[512];
#define TICK(i) do {} while (0)
constexpr int FL_EPOCH = 0, FL_TICKET = 1, FL_ERR = 2, FL_XN = 32, FL_U = 64, FL_H = 128, FL_Y = 256;

constexpr int STAGE_BYTES = 40960;
constexpr int NSTAGE = 4;
constexpr int OFF_U = NSTAGE * STAGE_BYTES;
constexpr int U_ZPAD = 896;
constexpr int U_PITCH = U_ZPAD + 4096;
constexpr int OFF_HC = OFF_U + 5 * U_PITCH;
constexpr int HC_PITCH = 8448;
constexpr int HC1_OFF = 4288;
constexpr int OFF_BAR = OFF_HC + 5 * HC_PITCH;
constexpr int SMEM_BYTES = OFF_BAR + 256;
constexpr int PS_BYTES = 4 * 8 * 264 * 4;
constexpr int OFF_XB = OFF_U;
constexpr int OFF_YT = OFF_U + 40960;
constexpr int B_FULL = 0, B_EMPTY = 4, B_HFULL = 8, B_UFULL = 9, B_XFREE = 10, B_XFULL = 11, B_YFULL = 12, B_HST = 13, B_STGFREE = 14, B_KVFULL = 15, B_KVFREE = 16, B_USIG = 17, B_YSIG = 18, NBAR = 19;
constexpr int OFF_KST = OFF_U, OFF_VST = OFF_U + 24576, OFF_UST = OFF_U + 45056;

__device__ __forceinline__ uint32_t smem_u32(const void* p) { return (uint32_t)__cvta_generic_to_shared(p); }
__device__ __forceinline__ void mbar_init(uint32_t a, int c) { asm volatile("mbarrier.init.shared::cta.b64 [%0], %1;" ::"r"(a), "r"(c)); }
__device__ __forceinline__ void mbar_expect_tx(uint32_t a, int b) { asm volatile("mbarrier.arrive.expect_tx.shared::cta.b64 _, [%0], %1;" ::"r"(a), "r"(b) : "memory"); }
__device__ __forceinline__ void mbar_arrive(uint32_t a) { asm volatile("mbarrier.arrive.shared::cta.b64 _, [%0];" ::"r"(a) : "memory"); }
__device__ __forceinline__ void mbar_arrive_remote(uint32_t a_cluster) { asm volatile("mbarrier.arrive.release.cluster.shared::cluster.b64 _, [%0];" ::"r"(a_cluster) : "memory"); }
__device__ __forceinline__ bool mbar_try(uint32_t a, int ph) {
    uint32_t ok;
    asm volatile("{\n.reg .pred p;\nmbarrier.try_wait.parity.shared::cta.b64 p, [%1], %2;\nselp.b32 %0, 1, 0, p;\n}\n" : "=r"(ok) : "r"(a), "r"(ph) : "memory");
    return ok;
}
__device__ __forceinline__ bool mbar_try_cluster(uint32_t a, int ph) {
    uint32_t ok;
    asm volatile("{\n.reg .pred p;\nmbarrier.try_wait.parity.acquire.cluster.shared::cta.b64 p, [%1], %2;\nselp.b32 %0, 1, 0, p;\n}\n" : "=r"(ok) : "r"(a), "r"(ph) : "memory");
    return ok;
}
constexpr long long WAIT_LIMIT = 60000000LL;
constexpr int SPIN_LIMIT = 1 << 22;
__device__ __forceinline__ void mbar_wait(uint32_t a, int ph) {
    #pragma unroll 1
    for (int i = 0; i < SPIN_LIMIT; i++) if (mbar_try(a, ph)) break;
}
__device__ __forceinline__ void mbar_wait_cluster(uint32_t a, int ph) {
    #pragma unroll 1
    for (int i = 0; i < SPIN_LIMIT; i++) if (mbar_try_cluster(a, ph)) break;
}
__device__ __forceinline__ unsigned ld_acquire(const unsigned* p) { unsigned v; asm volatile("ld.acquire.gpu.global.u32 %0, [%1];" : "=r"(v) : "l"(p) : "memory"); return v; }
__device__ __forceinline__ void st_release(unsigned* p, unsigned v) { asm volatile("st.release.gpu.global.u32 [%0], %1;" ::"l"(p), "r"(v) : "memory"); }
__device__ __forceinline__ void red_release_add(unsigned* p, unsigned v) { asm volatile("red.release.gpu.global.add.u32 [%0], %1;" ::"l"(p), "r"(v) : "memory"); }
__device__ __forceinline__ void flag_wait(const unsigned* p, unsigned target) {
    if ((int)(ld_acquire(p) - target) >= 0) return;
    long long t0 = clock64();
    while ((int)(ld_acquire(p) - target) < 0) { __nanosleep(20); if (clock64() - t0 > WAIT_LIMIT) { atomicExch(&g_flags[FL_ERR], 1u); break; } }
}
__device__ __forceinline__ void fence_proxy_async() { asm volatile("fence.proxy.async;" ::: "memory"); }
__device__ __forceinline__ void fence_proxy_async_smem() { asm volatile("fence.proxy.async.shared::cta;" ::: "memory"); }
__device__ __forceinline__ void bar_sync(int id, int n) { asm volatile("bar.sync %0, %1;" ::"r"(id), "r"(n) : "memory"); }

__device__ __forceinline__ void tma_load_2d(uint32_t dst, const CUtensorMap* tm, uint32_t bar, int c0, int c1) {
    asm volatile("cp.async.bulk.tensor.2d.shared::cluster.global.mbarrier::complete_tx::bytes [%0], [%1, {%3, %4}], [%2];"
                 ::"r"(dst), "l"(tm), "r"(bar), "r"(c0), "r"(c1) : "memory");
}
__device__ __forceinline__ void tma_store_2d(const CUtensorMap* tm, uint32_t src, int c0, int c1) {
    asm volatile("cp.async.bulk.tensor.2d.global.shared::cta.bulk_group [%0, {%2, %3}], [%1];" ::"l"(tm), "r"(src), "r"(c0), "r"(c1) : "memory");
}
__device__ __forceinline__ void bulk_load(uint32_t dst, const void* src, int bytes, uint32_t bar) {
    asm volatile("cp.async.bulk.shared::cluster.global.mbarrier::complete_tx::bytes [%0], [%1], %2, [%3];" ::"r"(dst), "l"(src), "r"(bytes), "r"(bar) : "memory");
}
__device__ __forceinline__ void bulk_prefetch_l2(const void* src, int bytes) {
    asm volatile("cp.async.bulk.prefetch.L2.global [%0], %1;" ::"l"(src), "r"(bytes) : "memory");
}
__device__ __forceinline__ void bulk_commit() { asm volatile("cp.async.bulk.commit_group;" ::: "memory"); }
__device__ __forceinline__ void bulk_wait0() { asm volatile("cp.async.bulk.wait_group 0;" ::: "memory"); }

__device__ __forceinline__ uint64_t make_desc(uint32_t saddr, uint32_t lbo, uint32_t sbo, uint32_t swz) {
    uint64_t d = 0;
    d |= (uint64_t)((saddr & 0x3FFFF) >> 4);
    d |= (uint64_t)((lbo & 0x3FFFF) >> 4) << 16;
    d |= (uint64_t)((sbo & 0x3FFFF) >> 4) << 32;
    d |= (uint64_t)swz << 62;
    return d;
}
__device__ __forceinline__ void wg_fence() { asm volatile("wgmma.fence.sync.aligned;" ::: "memory"); }
__device__ __forceinline__ void wg_commit() { asm volatile("wgmma.commit_group.sync.aligned;" ::: "memory"); }
template <int N> __device__ __forceinline__ void wg_wait() { asm volatile("wgmma.wait_group.sync.aligned %0;" ::"n"(N) : "memory"); }
template <int R> __device__ __forceinline__ void reg_alloc() { asm volatile("setmaxnreg.inc.sync.aligned.u32 %0;" ::"n"(R)); }
template <int R> __device__ __forceinline__ void reg_dealloc() { asm volatile("setmaxnreg.dec.sync.aligned.u32 %0;" ::"n"(R)); }
__device__ __forceinline__ void stmatrix_x4(uint32_t addr, uint32_t r0, uint32_t r1, uint32_t r2, uint32_t r3) {
    asm volatile("stmatrix.sync.aligned.m8n8.x4.shared.b16 [%0], {%1, %2, %3, %4};" ::"r"(addr), "r"(r0), "r"(r1), "r"(r2), "r"(r3) : "memory");
}
__device__ __forceinline__ uint32_t lds32(uint32_t a) { uint32_t v; asm volatile("ld.shared.b32 %0, [%1];" : "=r"(v) : "r"(a)); return v; }
__device__ __forceinline__ uint4 lds128(uint32_t a) { uint4 v; asm volatile("ld.shared.v4.b32 {%0,%1,%2,%3}, [%4];" : "=r"(v.x), "=r"(v.y), "=r"(v.z), "=r"(v.w) : "r"(a)); return v; }
__device__ __forceinline__ uint2 lds64(uint32_t a) { uint2 v; asm volatile("ld.shared.v2.b32 {%0,%1}, [%2];" : "=r"(v.x), "=r"(v.y) : "r"(a)); return v; }
__device__ __forceinline__ void sts128(uint32_t a, uint4 v) { asm volatile("st.shared.v4.b32 [%0], {%1,%2,%3,%4};" ::"r"(a), "r"(v.x), "r"(v.y), "r"(v.z), "r"(v.w) : "memory"); }
__device__ __forceinline__ uint32_t pack_bf16(float lo, float hi) { __nv_bfloat162 t = __floats2bfloat162_rn(lo, hi); return *reinterpret_cast<uint32_t*>(&t); }
__device__ __forceinline__ float bf16r(float v) { return __bfloat162float(__float2bfloat16_rn(v)); }
__device__ __forceinline__ float div_nr(float a, float d, float rd) { float q = a * rd; float r = fmaf(-q, d, a); return fmaf(r, rd, q); }
__device__ __forceinline__ float bf_lo(uint32_t v) { return __uint_as_float(v << 16); }
__device__ __forceinline__ float bf_hi(uint32_t v) { return __uint_as_float(v & 0xffff0000u); }

__device__ __forceinline__ void wgmma_rs_n64(float* d, uint32_t a0, uint32_t a1, uint32_t a2, uint32_t a3, uint64_t db, int sd) {
  asm volatile("{\n.reg .pred p;\nsetp.ne.b32 p, %37, 0;\n"
    "wgmma.mma_async.sync.aligned.m64n64k16.f32.bf16.bf16 {%0, %1, %2, %3, %4, %5, %6, %7, %8, %9, %10, %11, %12, %13, %14, %15, %16, %17, %18, %19, %20, %21, %22, %23, %24, %25, %26, %27, %28, %29, %30, %31}, {%32, %33, %34, %35}, %36, p, 1, 1, 0;\n}\n"
    : "+f"(d[0]), "+f"(d[1]), "+f"(d[2]), "+f"(d[3]), "+f"(d[4]), "+f"(d[5]), "+f"(d[6]), "+f"(d[7]), "+f"(d[8]), "+f"(d[9]), "+f"(d[10]), "+f"(d[11]), "+f"(d[12]), "+f"(d[13]), "+f"(d[14]), "+f"(d[15]), "+f"(d[16]), "+f"(d[17]), "+f"(d[18]), "+f"(d[19]), "+f"(d[20]), "+f"(d[21]), "+f"(d[22]), "+f"(d[23]), "+f"(d[24]), "+f"(d[25]), "+f"(d[26]), "+f"(d[27]), "+f"(d[28]), "+f"(d[29]), "+f"(d[30]), "+f"(d[31])
    : "r"(a0), "r"(a1), "r"(a2), "r"(a3), "l"(db), "r"(sd));
}
__device__ __forceinline__ void wgmma_ss_tb_n192(float* d, uint64_t da, uint64_t db, int sd) {
  asm volatile("{\n.reg .pred p;\nsetp.ne.b32 p, %98, 0;\n"
    "wgmma.mma_async.sync.aligned.m64n192k16.f32.bf16.bf16 {%0, %1, %2, %3, %4, %5, %6, %7, %8, %9, %10, %11, %12, %13, %14, %15, %16, %17, %18, %19, %20, %21, %22, %23, %24, %25, %26, %27, %28, %29, %30, %31, %32, %33, %34, %35, %36, %37, %38, %39, %40, %41, %42, %43, %44, %45, %46, %47, %48, %49, %50, %51, %52, %53, %54, %55, %56, %57, %58, %59, %60, %61, %62, %63, %64, %65, %66, %67, %68, %69, %70, %71, %72, %73, %74, %75, %76, %77, %78, %79, %80, %81, %82, %83, %84, %85, %86, %87, %88, %89, %90, %91, %92, %93, %94, %95}, %96, %97, p, 1, 1, 0, 1;\n}\n"
    : "+f"(d[0]), "+f"(d[1]), "+f"(d[2]), "+f"(d[3]), "+f"(d[4]), "+f"(d[5]), "+f"(d[6]), "+f"(d[7]), "+f"(d[8]), "+f"(d[9]), "+f"(d[10]), "+f"(d[11]), "+f"(d[12]), "+f"(d[13]), "+f"(d[14]), "+f"(d[15]), "+f"(d[16]), "+f"(d[17]), "+f"(d[18]), "+f"(d[19]), "+f"(d[20]), "+f"(d[21]), "+f"(d[22]), "+f"(d[23]), "+f"(d[24]), "+f"(d[25]), "+f"(d[26]), "+f"(d[27]), "+f"(d[28]), "+f"(d[29]), "+f"(d[30]), "+f"(d[31]), "+f"(d[32]), "+f"(d[33]), "+f"(d[34]), "+f"(d[35]), "+f"(d[36]), "+f"(d[37]), "+f"(d[38]), "+f"(d[39]), "+f"(d[40]), "+f"(d[41]), "+f"(d[42]), "+f"(d[43]), "+f"(d[44]), "+f"(d[45]), "+f"(d[46]), "+f"(d[47]), "+f"(d[48]), "+f"(d[49]), "+f"(d[50]), "+f"(d[51]), "+f"(d[52]), "+f"(d[53]), "+f"(d[54]), "+f"(d[55]), "+f"(d[56]), "+f"(d[57]), "+f"(d[58]), "+f"(d[59]), "+f"(d[60]), "+f"(d[61]), "+f"(d[62]), "+f"(d[63]), "+f"(d[64]), "+f"(d[65]), "+f"(d[66]), "+f"(d[67]), "+f"(d[68]), "+f"(d[69]), "+f"(d[70]), "+f"(d[71]), "+f"(d[72]), "+f"(d[73]), "+f"(d[74]), "+f"(d[75]), "+f"(d[76]), "+f"(d[77]), "+f"(d[78]), "+f"(d[79]), "+f"(d[80]), "+f"(d[81]), "+f"(d[82]), "+f"(d[83]), "+f"(d[84]), "+f"(d[85]), "+f"(d[86]), "+f"(d[87]), "+f"(d[88]), "+f"(d[89]), "+f"(d[90]), "+f"(d[91]), "+f"(d[92]), "+f"(d[93]), "+f"(d[94]), "+f"(d[95])
    : "l"(da), "l"(db), "r"(sd));
}
__device__ __forceinline__ void wgmma_ss_tb_n160(float* d, uint64_t da, uint64_t db, int sd) {
  asm volatile("{\n.reg .pred p;\nsetp.ne.b32 p, %82, 0;\n"
    "wgmma.mma_async.sync.aligned.m64n160k16.f32.bf16.bf16 {%0, %1, %2, %3, %4, %5, %6, %7, %8, %9, %10, %11, %12, %13, %14, %15, %16, %17, %18, %19, %20, %21, %22, %23, %24, %25, %26, %27, %28, %29, %30, %31, %32, %33, %34, %35, %36, %37, %38, %39, %40, %41, %42, %43, %44, %45, %46, %47, %48, %49, %50, %51, %52, %53, %54, %55, %56, %57, %58, %59, %60, %61, %62, %63, %64, %65, %66, %67, %68, %69, %70, %71, %72, %73, %74, %75, %76, %77, %78, %79}, %80, %81, p, 1, 1, 0, 1;\n}\n"
    : "+f"(d[0]), "+f"(d[1]), "+f"(d[2]), "+f"(d[3]), "+f"(d[4]), "+f"(d[5]), "+f"(d[6]), "+f"(d[7]), "+f"(d[8]), "+f"(d[9]), "+f"(d[10]), "+f"(d[11]), "+f"(d[12]), "+f"(d[13]), "+f"(d[14]), "+f"(d[15]), "+f"(d[16]), "+f"(d[17]), "+f"(d[18]), "+f"(d[19]), "+f"(d[20]), "+f"(d[21]), "+f"(d[22]), "+f"(d[23]), "+f"(d[24]), "+f"(d[25]), "+f"(d[26]), "+f"(d[27]), "+f"(d[28]), "+f"(d[29]), "+f"(d[30]), "+f"(d[31]), "+f"(d[32]), "+f"(d[33]), "+f"(d[34]), "+f"(d[35]), "+f"(d[36]), "+f"(d[37]), "+f"(d[38]), "+f"(d[39]), "+f"(d[40]), "+f"(d[41]), "+f"(d[42]), "+f"(d[43]), "+f"(d[44]), "+f"(d[45]), "+f"(d[46]), "+f"(d[47]), "+f"(d[48]), "+f"(d[49]), "+f"(d[50]), "+f"(d[51]), "+f"(d[52]), "+f"(d[53]), "+f"(d[54]), "+f"(d[55]), "+f"(d[56]), "+f"(d[57]), "+f"(d[58]), "+f"(d[59]), "+f"(d[60]), "+f"(d[61]), "+f"(d[62]), "+f"(d[63]), "+f"(d[64]), "+f"(d[65]), "+f"(d[66]), "+f"(d[67]), "+f"(d[68]), "+f"(d[69]), "+f"(d[70]), "+f"(d[71]), "+f"(d[72]), "+f"(d[73]), "+f"(d[74]), "+f"(d[75]), "+f"(d[76]), "+f"(d[77]), "+f"(d[78]), "+f"(d[79])
    : "l"(da), "l"(db), "r"(sd));
}
#define CONV_MMA_CHAIN(acc, A, db) \
  wgmma_rs_n64((acc) + 0, (A)[0], (A)[1], (A)[2], (A)[3], (db) + (0), 0); \
  wgmma_rs_n64((acc) + 32, (A)[0], (A)[1], (A)[2], (A)[3], (db) + (64), 0); \
  wgmma_rs_n64((acc) + 64, (A)[0], (A)[1], (A)[2], (A)[3], (db) + (128), 0); \
  wgmma_rs_n64((acc) + 96, (A)[0], (A)[1], (A)[2], (A)[3], (db) + (192), 0); \
  wgmma_rs_n64((acc) + 0, (A)[4], (A)[5], (A)[6], (A)[7], (db) + (-16), 1); \
  wgmma_rs_n64((acc) + 32, (A)[4], (A)[5], (A)[6], (A)[7], (db) + (48), 1); \
  wgmma_rs_n64((acc) + 64, (A)[4], (A)[5], (A)[6], (A)[7], (db) + (112), 1); \
  wgmma_rs_n64((acc) + 96, (A)[4], (A)[5], (A)[6], (A)[7], (db) + (176), 1); \
  wgmma_rs_n64((acc) + 0, (A)[8], (A)[9], (A)[10], (A)[11], (db) + (-32), 1); \
  wgmma_rs_n64((acc) + 32, (A)[8], (A)[9], (A)[10], (A)[11], (db) + (32), 1); \
  wgmma_rs_n64((acc) + 64, (A)[8], (A)[9], (A)[10], (A)[11], (db) + (96), 1); \
  wgmma_rs_n64((acc) + 96, (A)[8], (A)[9], (A)[10], (A)[11], (db) + (160), 1); \
  wgmma_rs_n64((acc) + 0, (A)[12], (A)[13], (A)[14], (A)[15], (db) + (-48), 1); \
  wgmma_rs_n64((acc) + 32, (A)[12], (A)[13], (A)[14], (A)[15], (db) + (16), 1); \
  wgmma_rs_n64((acc) + 64, (A)[12], (A)[13], (A)[14], (A)[15], (db) + (80), 1); \
  wgmma_rs_n64((acc) + 96, (A)[12], (A)[13], (A)[14], (A)[15], (db) + (144), 1); \
  wgmma_rs_n64((acc) + 32, (A)[16], (A)[17], (A)[18], (A)[19], (db) + (0), 1); \
  wgmma_rs_n64((acc) + 64, (A)[16], (A)[17], (A)[18], (A)[19], (db) + (64), 1); \
  wgmma_rs_n64((acc) + 96, (A)[16], (A)[17], (A)[18], (A)[19], (db) + (128), 1); \
  wgmma_rs_n64((acc) + 32, (A)[20], (A)[21], (A)[22], (A)[23], (db) + (-16), 1); \
  wgmma_rs_n64((acc) + 64, (A)[20], (A)[21], (A)[22], (A)[23], (db) + (48), 1); \
  wgmma_rs_n64((acc) + 96, (A)[20], (A)[21], (A)[22], (A)[23], (db) + (112), 1); \
  wgmma_rs_n64((acc) + 32, (A)[24], (A)[25], (A)[26], (A)[27], (db) + (-32), 1); \
  wgmma_rs_n64((acc) + 64, (A)[24], (A)[25], (A)[26], (A)[27], (db) + (32), 1); \
  wgmma_rs_n64((acc) + 96, (A)[24], (A)[25], (A)[26], (A)[27], (db) + (96), 1); \
  wgmma_rs_n64((acc) + 32, (A)[28], (A)[29], (A)[30], (A)[31], (db) + (-48), 1); \
  wgmma_rs_n64((acc) + 64, (A)[28], (A)[29], (A)[30], (A)[31], (db) + (16), 1); \
  wgmma_rs_n64((acc) + 96, (A)[28], (A)[29], (A)[30], (A)[31], (db) + (80), 1); \
  wgmma_rs_n64((acc) + 64, (A)[32], (A)[33], (A)[34], (A)[35], (db) + (0), 1); \
  wgmma_rs_n64((acc) + 96, (A)[32], (A)[33], (A)[34], (A)[35], (db) + (64), 1); \
  wgmma_rs_n64((acc) + 64, (A)[36], (A)[37], (A)[38], (A)[39], (db) + (-16), 1); \
  wgmma_rs_n64((acc) + 96, (A)[36], (A)[37], (A)[38], (A)[39], (db) + (48), 1); \
  wgmma_rs_n64((acc) + 64, (A)[40], (A)[41], (A)[42], (A)[43], (db) + (-32), 1); \
  wgmma_rs_n64((acc) + 96, (A)[40], (A)[41], (A)[42], (A)[43], (db) + (32), 1); \
  wgmma_rs_n64((acc) + 64, (A)[44], (A)[45], (A)[46], (A)[47], (db) + (-48), 1); \
  wgmma_rs_n64((acc) + 96, (A)[44], (A)[45], (A)[46], (A)[47], (db) + (16), 1); \
  wgmma_rs_n64((acc) + 96, (A)[48], (A)[49], (A)[50], (A)[51], (db) + (0), 1); \
  wgmma_rs_n64((acc) + 96, (A)[52], (A)[53], (A)[54], (A)[55], (db) + (-16), 1); \
  wgmma_rs_n64((acc) + 96, (A)[56], (A)[57], (A)[58], (A)[59], (db) + (-32), 1); \
  wgmma_rs_n64((acc) + 96, (A)[60], (A)[61], (A)[62], (A)[63], (db) + (-48), 1);
#define CONV_CHAIN_WG0(acc, A, db) \
  wgmma_rs_n64((acc) + 0, (A)[0], (A)[1], (A)[2], (A)[3], (db) + (0), 0); \
  wgmma_rs_n64((acc) + 32, (A)[0], (A)[1], (A)[2], (A)[3], (db) + (192), 0); \
  wgmma_rs_n64((acc) + 0, (A)[4], (A)[5], (A)[6], (A)[7], (db) + (-16), 1); \
  wgmma_rs_n64((acc) + 32, (A)[4], (A)[5], (A)[6], (A)[7], (db) + (176), 1); \
  wgmma_rs_n64((acc) + 0, (A)[8], (A)[9], (A)[10], (A)[11], (db) + (-32), 1); \
  wgmma_rs_n64((acc) + 32, (A)[8], (A)[9], (A)[10], (A)[11], (db) + (160), 1); \
  wgmma_rs_n64((acc) + 0, (A)[12], (A)[13], (A)[14], (A)[15], (db) + (-48), 1); \
  wgmma_rs_n64((acc) + 32, (A)[12], (A)[13], (A)[14], (A)[15], (db) + (144), 1); \
  wgmma_rs_n64((acc) + 32, (A)[16], (A)[17], (A)[18], (A)[19], (db) + (128), 1); \
  wgmma_rs_n64((acc) + 32, (A)[20], (A)[21], (A)[22], (A)[23], (db) + (112), 1); \
  wgmma_rs_n64((acc) + 32, (A)[24], (A)[25], (A)[26], (A)[27], (db) + (96), 1); \
  wgmma_rs_n64((acc) + 32, (A)[28], (A)[29], (A)[30], (A)[31], (db) + (80), 1); \
  wgmma_rs_n64((acc) + 32, (A)[32], (A)[33], (A)[34], (A)[35], (db) + (64), 1); \
  wgmma_rs_n64((acc) + 32, (A)[36], (A)[37], (A)[38], (A)[39], (db) + (48), 1); \
  wgmma_rs_n64((acc) + 32, (A)[40], (A)[41], (A)[42], (A)[43], (db) + (32), 1); \
  wgmma_rs_n64((acc) + 32, (A)[44], (A)[45], (A)[46], (A)[47], (db) + (16), 1); \
  wgmma_rs_n64((acc) + 32, (A)[48], (A)[49], (A)[50], (A)[51], (db) + (0), 1); \
  wgmma_rs_n64((acc) + 32, (A)[52], (A)[53], (A)[54], (A)[55], (db) + (-16), 1); \
  wgmma_rs_n64((acc) + 32, (A)[56], (A)[57], (A)[58], (A)[59], (db) + (-32), 1); \
  wgmma_rs_n64((acc) + 32, (A)[60], (A)[61], (A)[62], (A)[63], (db) + (-48), 1);
#define CONV_CHAIN_WG1(acc, A, db) \
  wgmma_rs_n64((acc) + 0, (A)[0], (A)[1], (A)[2], (A)[3], (db) + (64), 0); \
  wgmma_rs_n64((acc) + 32, (A)[0], (A)[1], (A)[2], (A)[3], (db) + (128), 0); \
  wgmma_rs_n64((acc) + 0, (A)[4], (A)[5], (A)[6], (A)[7], (db) + (48), 1); \
  wgmma_rs_n64((acc) + 32, (A)[4], (A)[5], (A)[6], (A)[7], (db) + (112), 1); \
  wgmma_rs_n64((acc) + 0, (A)[8], (A)[9], (A)[10], (A)[11], (db) + (32), 1); \
  wgmma_rs_n64((acc) + 32, (A)[8], (A)[9], (A)[10], (A)[11], (db) + (96), 1); \
  wgmma_rs_n64((acc) + 0, (A)[12], (A)[13], (A)[14], (A)[15], (db) + (16), 1); \
  wgmma_rs_n64((acc) + 32, (A)[12], (A)[13], (A)[14], (A)[15], (db) + (80), 1); \
  wgmma_rs_n64((acc) + 0, (A)[16], (A)[17], (A)[18], (A)[19], (db) + (0), 1); \
  wgmma_rs_n64((acc) + 32, (A)[16], (A)[17], (A)[18], (A)[19], (db) + (64), 1); \
  wgmma_rs_n64((acc) + 0, (A)[20], (A)[21], (A)[22], (A)[23], (db) + (-16), 1); \
  wgmma_rs_n64((acc) + 32, (A)[20], (A)[21], (A)[22], (A)[23], (db) + (48), 1); \
  wgmma_rs_n64((acc) + 0, (A)[24], (A)[25], (A)[26], (A)[27], (db) + (-32), 1); \
  wgmma_rs_n64((acc) + 32, (A)[24], (A)[25], (A)[26], (A)[27], (db) + (32), 1); \
  wgmma_rs_n64((acc) + 0, (A)[28], (A)[29], (A)[30], (A)[31], (db) + (-48), 1); \
  wgmma_rs_n64((acc) + 32, (A)[28], (A)[29], (A)[30], (A)[31], (db) + (16), 1); \
  wgmma_rs_n64((acc) + 32, (A)[32], (A)[33], (A)[34], (A)[35], (db) + (0), 1); \
  wgmma_rs_n64((acc) + 32, (A)[36], (A)[37], (A)[38], (A)[39], (db) + (-16), 1); \
  wgmma_rs_n64((acc) + 32, (A)[40], (A)[41], (A)[42], (A)[43], (db) + (-32), 1); \
  wgmma_rs_n64((acc) + 32, (A)[44], (A)[45], (A)[46], (A)[47], (db) + (-48), 1);

struct KParams {
    const __nv_bfloat16 *x, *k, *v, *shift_k, *ssm_k, *ssm_D, *w1, *w2;
    __nv_bfloat16* out;
};

__device__ __forceinline__ void bar_arrive(int id, int n) { asm volatile("bar.arrive %0, %1;" ::"r"(id), "r"(n) : "memory"); }

__global__ void __launch_bounds__(NTHREADS, 1)
fused_kernel(const __grid_constant__ CUtensorMap tm_xn, const __grid_constant__ CUtensorMap tm_w1,
             const __grid_constant__ CUtensorMap tm_h, const __grid_constant__ CUtensorMap tm_w2,
             const __grid_constant__ CUtensorMap tm_y2T, const __grid_constant__ CUtensorMap tm_xe,
             const __grid_constant__ CUtensorMap tm_xne, const __grid_constant__ CUtensorMap tm_uT, const __grid_constant__ CUtensorMap tm_out, const KParams P) {
    extern __shared__ __align__(1024) uint8_t smem[];
    const uint32_t sb = smem_u32(smem);
    const uint32_t bars = sb + OFF_BAR;
    const int tid = threadIdx.x, lane = tid & 31, warp = tid >> 5, wg = tid >> 7;
    const int cta = blockIdx.x;
    const int rb = cta >> 3;
    const int jn = cta & 7;
    const int kh = cta & 1;
    const int cb = (cta >> 1) & 3;
    const int ct = tid - 128;
    const int cw = ct >> 5;

    uint2 xv[2][5];
    uint4 wa = make_uint4(0,0,0,0), wb = make_uint4(0,0,0,0);
    if (wg != 0) {
        #pragma unroll
        for (int rr = 0; rr < 2; rr++) {
            const uint2* xr = reinterpret_cast<const uint2*>(P.x + (size_t)(cta * 16 + cw * 2 + rr) * D_);
            #pragma unroll
            for (int q = 0; q < 5; q++) xv[rr][q] = __ldg(xr + q * 32 + lane);
        }
        if (ct < 160) {
            wa = __ldg(reinterpret_cast<const uint4*>(P.shift_k + ct * 16));
            wb = __ldg(reinterpret_cast<const uint4*>(P.shift_k + ct * 16 + 8));
        }
    }

    if (tid == 0) {
        for (int i = 0; i < 4; i++) { mbar_init(bars + 8 * (B_FULL + i), 1); mbar_init(bars + 8 * (B_EMPTY + i), 8); }
        mbar_init(bars + 8 * B_HFULL, 1); mbar_init(bars + 8 * B_UFULL, 1);
        mbar_init(bars + 8 * B_XFREE, 8); mbar_init(bars + 8 * B_XFULL, 8); mbar_init(bars + 8 * B_YFULL, 1);
        mbar_init(bars + 8 * B_HST, 8); mbar_init(bars + 8 * B_STGFREE, 1);
        mbar_init(bars + 8 * B_KVFULL, 1); mbar_init(bars + 8 * B_KVFREE, 5); mbar_init(bars + 8 * B_USIG, 5); mbar_init(bars + 8 * B_YSIG, 8);
        asm volatile("fence.mbarrier_init.release.cluster;" ::: "memory");
    }
    unsigned epoch; asm volatile("ld.relaxed.gpu.global.u32 %0, [%1];" : "=r"(epoch) : "l"(&g_flags[FL_EPOCH]) : "memory");
    const unsigned ep1 = epoch + 1;
    __syncthreads();
    asm volatile("barrier.cluster.arrive.relaxed.aligned;" ::: "memory");

    if (wg == 0) {
        reg_dealloc<40>();
        if (warp == 0) {
            int it = 0;
            if (lane == 0) {
                const int r0 = cta ? cta * 16 - 3 : 0, nr = cta ? 19 : 16;
                mbar_expect_tx(bars + 8 * B_KVFULL, (nr + 16) * 1280);
                bulk_load(sb + OFF_KST + (19 - nr) * 1280, P.k + (size_t)r0 * D_, nr * 1280, bars + 8 * B_KVFULL);
                bulk_load(sb + OFF_VST, P.v + (size_t)cta * 16 * D_, 16 * 1280, bars + 8 * B_KVFULL);
                for (int kb = 0; kb < 4; kb++) {
                    uint32_t st = sb + kb * STAGE_BYTES;
                    mbar_expect_tx(bars + 8 * (B_FULL + kb), 16384 + 24576);
                    for (int q = 0; q < 3; q++) tma_load_2d(st + 16384 + q * 8192, &tm_w1, bars + 8 * (B_FULL + kb), jn * 192 + q * 64, kb * 64);
                }
                bulk_prefetch_l2(reinterpret_cast<const uint8_t*>(P.w1) + (size_t)cta * 15360, 15360);
                flag_wait(&g_flags[FL_XN + rb], 8u * ep1);
                fence_proxy_async();
                for (int kb = 0; kb < 4; kb++) tma_load_2d(sb + kb * STAGE_BYTES, &tm_xn, bars + 8 * (B_FULL + kb), kb * 64, rb * 128);
                bulk_prefetch_l2(P.ssm_k + (size_t)cta * 5 * S_, 5 * 4096);
                bulk_prefetch_l2(reinterpret_cast<const uint8_t*>(P.w2) + (size_t)cta * 15360, 15360);
                it = 4;
                for (int kb = 4; kb < 10; kb++, it++) {
                    int s = it & 3;
                    mbar_wait(bars + 8 * (B_EMPTY + s), ((it >> 2) - 1) & 1);
                    uint32_t st = sb + s * STAGE_BYTES;
                    mbar_expect_tx(bars + 8 * (B_FULL + s), 16384 + 24576);
                    for (int q = 0; q < 3; q++) tma_load_2d(st + 16384 + q * 8192, &tm_w1, bars + 8 * (B_FULL + s), jn * 192 + q * 64, kb * 64);
                    tma_load_2d(st, &tm_xn, bars + 8 * (B_FULL + s), kb * 64, rb * 128);
                }
            }
            __syncwarp();
            if (lane == 0) {
                flag_wait(&g_flags[FL_U], (unsigned)NCTA * ep1);
                fence_proxy_async();
                mbar_expect_tx(bars + 8 * B_UFULL, 5 * 4096);
                for (int ch = 0; ch < 5; ch++)
                    bulk_load(sb + OFF_U + ch * U_PITCH + U_ZPAD, g_uT + (size_t)(cta * 5 + ch) * S_, 4096, bars + 8 * B_UFULL);
            }
            __syncwarp();
            if (lane < 4) flag_wait(&g_flags[FL_H + rb * 8 + kh * 4 + lane], ep1);
            __syncwarp();
            if (lane == 0) {
                fence_proxy_async();
                it = 10;
                for (int kb = 0; kb < 12; kb++, it++) {
                    int s = it & 3;
                    mbar_wait(bars + 8 * (B_EMPTY + s), ((it >> 2) - 1) & 1);
                    uint32_t st = sb + s * STAGE_BYTES;
                    mbar_expect_tx(bars + 8 * (B_FULL + s), 16384 + 20480);
                    for (int q = 0; q < 5; q++) tma_load_2d(st + 16384 + q * 4096, &tm_w2, bars + 8 * (B_FULL + s), cb * 160 + q * 32, kh * 768 + kb * 64);
                    tma_load_2d(st, &tm_h, bars + 8 * (B_FULL + s), kh * 768 + kb * 64, rb * 128);
                }
                {
                    int s = it & 3;
                    mbar_wait(bars + 8 * (B_EMPTY + s), ((it >> 2) - 1) & 1);
                    uint32_t st = sb + s * STAGE_BYTES;
                    mbar_expect_tx(bars + 8 * (B_FULL + s), 2 * 20480);
                    tma_load_2d(st, &tm_xe, bars + 8 * (B_FULL + s), cb * 160 + kh * 80, rb * 128);
                    tma_load_2d(st + 20480, &tm_xne, bars + 8 * (B_FULL + s), cb * 160 + kh * 80, rb * 128);
                }
            }
            __syncwarp();
            if (lane < 16) flag_wait(&g_flags[FL_Y + cb * 32 + kh * 16 + lane], ep1);
            __syncwarp();
            if (lane == 0) {
                fence_proxy_async();
                mbar_expect_tx(bars + 8 * B_YFULL, 20480);
                for (int q = 0; q < 2; q++) tma_load_2d(sb + OFF_YT + q * 10240, &tm_y2T, bars + 8 * B_YFULL, rb * 128 + q * 64, cb * 160 + kh * 80);
            }
            __syncwarp();
        } else if (warp == 1) {
            if (lane == 0) {
                mbar_wait(bars + 8 * B_HST, 0);
                for (int q = 0; q < 3; q++) tma_store_2d(&tm_h, sb + q * 16384, jn * 192 + q * 64, rb * 128);
                bulk_commit();
                bulk_wait0();
                mbar_arrive(bars + 8 * B_STGFREE);
                __threadfence();
                st_release(&g_flags[FL_H + cta], ep1);
            }
            __syncwarp();
        } else if (warp == 2) {
            if (lane == 0) {
                mbar_wait(bars + 8 * B_USIG, 0);
                for (int q = 0; q < 5; q++) tma_store_2d(&tm_uT, sb + OFF_UST + q * 4096, cta * 16, q * 128);
                bulk_commit();
                mbar_wait(bars + 8 * B_KVFREE, 0);
                asm volatile("cp.async.bulk.wait_group.read 0;" ::: "memory");
            }
            __syncwarp();
            for (int i = lane; i < 280; i += 32) sts128(sb + OFF_U + (i / 56) * U_PITCH + (i % 56) * 16, make_uint4(0, 0, 0, 0));
            if (lane < 10) sts128(sb + OFF_HC + (lane >> 1) * HC_PITCH + (lane & 1) * HC1_OFF, make_uint4(0, 0, 0, 0));
            fence_proxy_async_smem();
            __syncwarp();
            if (lane == 0) {
                mbar_expect_tx(bars + 8 * B_HFULL, 5 * 4096);
                for (int ch = 0; ch < 5; ch++)
                    bulk_load(sb + OFF_HC + ch * HC_PITCH + 16, P.ssm_k + (size_t)(cta * 5 + ch) * S_, 4096, bars + 8 * B_HFULL);
                bulk_wait0();
                __threadfence();
                red_release_add(&g_flags[FL_U], 1u);
            }
            __syncwarp();
        } else {
            if (lane == 0) {
                mbar_wait(bars + 8 * B_YSIG, 0);
                red_release_add(&g_flags[FL_Y + cta], 1u);
            }
            __syncwarp();
        }
    } else {
        reg_alloc<232>();
        const int wgc = __shfl_sync(0xffffffffu, wg - 1, 0);
        const int w4 = cw & 3;
        const int g4 = lane >> 2, c4 = lane & 3;
        TICK(0);

        {
            #pragma unroll 1
            for (int rr = 0; rr < 2; rr++) {
                float f[20];
                #pragma unroll
                for (int q = 0; q < 5; q++) { uint2 w = rr ? xv[1][q] : xv[0][q]; f[4*q] = bf_lo(w.x); f[4*q+1] = bf_hi(w.x); f[4*q+2] = bf_lo(w.y); f[4*q+3] = bf_hi(w.y); }
                float s0 = 0.f, s1 = 0.f, s2 = 0.f, s3 = 0.f;
                #pragma unroll
                for (int q = 0; q < 5; q++) { s0 += f[4*q]; s1 += f[4*q+1]; s2 += f[4*q+2]; s3 += f[4*q+3]; }
                float mean = (s0 + s1) + (s2 + s3);
                #pragma unroll
                for (int o = 16; o; o >>= 1) mean += __shfl_xor_sync(0xffffffffu, mean, o);
                mean *= (1.0f / 640.0f);
                s0 = 0.f; s1 = 0.f; s2 = 0.f; s3 = 0.f;
                #pragma unroll
                for (int q = 0; q < 5; q++) {
                    float d0 = f[4*q] - mean, d1 = f[4*q+1] - mean, d2 = f[4*q+2] - mean, d3 = f[4*q+3] - mean;
                    s0 = fmaf(d0, d0, s0); s1 = fmaf(d1, d1, s1); s2 = fmaf(d2, d2, s2); s3 = fmaf(d3, d3, s3);
                }
                float vs = (s0 + s1) + (s2 + s3);
                #pragma unroll
                for (int o = 16; o; o >>= 1) vs += __shfl_xor_sync(0xffffffffu, vs, o);
                const float mb = bf16r(mean);
                const float vb = bf16r(vs * (1.0f / 640.0f));
                const float den = bf16r(sqrtf(bf16r(vb + 1e-5f)));
                const float rden = __frcp_rn(den);
                uint2* xo = reinterpret_cast<uint2*>(g_xn + (size_t)(cta * 16 + cw * 2 + rr) * D_);
                #pragma unroll
                for (int q = 0; q < 5; q++) {
                    float a0 = bf16r(f[4*q] - mb), a1 = bf16r(f[4*q+1] - mb), a2 = bf16r(f[4*q+2] - mb), a3 = bf16r(f[4*q+3] - mb);
                    uint2 o; o.x = pack_bf16(div_nr(a0, den, rden), div_nr(a1, den, rden)); o.y = pack_bf16(div_nr(a2, den, rden), div_nr(a3, den, rden));
                    xo[q * 32 + lane] = o;
                }
            }
            TICK(18);
            bar_sync(1, 256);
            if (ct == 255) red_release_add(&g_flags[FL_XN + rb], 1u);
            TICK(1);
        }
        TICK(3);
        {
            uint32_t wp[2][4];
            #pragma unroll 1
            for (int qd = 0; qd < 4; qd++) {
            if (ct < 160) {
                const int p = qd >> 1, g = qd & 1;
                if (qd == 0) {
                    mbar_wait(bars + 8 * B_KVFULL, 0);
                    TICK(29);
                    wp[0][0] = __byte_perm(wa.x, wa.z, 0x5410); wp[0][1] = __byte_perm(wa.x, wa.z, 0x7632);
                    wp[0][2] = __byte_perm(wa.y, wa.w, 0x5410); wp[0][3] = __byte_perm(wa.y, wa.w, 0x7632);
                    wp[1][0] = __byte_perm(wb.x, wb.z, 0x5410); wp[1][1] = __byte_perm(wb.x, wb.z, 0x7632);
                    wp[1][2] = __byte_perm(wb.y, wb.w, 0x5410); wp[1][3] = __byte_perm(wb.y, wb.w, 0x7632);
                }
                uint32_t kq[11], vq[8], u[8];
                #pragma unroll
                for (int i = 0; i < 11; i++) kq[i] = (cta > 0 || g > 0 || i >= 3) ? lds32(sb + OFF_KST + (8 * g + i) * 1280 + ct * 8 + p * 4) : 0u;
                #pragma unroll
                for (int i = 0; i < 8; i++) vq[i] = lds32(sb + OFF_VST + (8 * g + i) * 1280 + ct * 8 + p * 4);
                const uint32_t w3 = p ? wp[1][3] : wp[0][3], w2 = p ? wp[1][2] : wp[0][2], w1 = p ? wp[1][1] : wp[0][1], w0 = p ? wp[1][0] : wp[0][0];
                #pragma unroll
                for (int i = 0; i < 8; i++) {
                    auto bf = [](uint32_t r) { return *reinterpret_cast<__nv_bfloat162*>(&r); };
                    __nv_bfloat162 a = __hmul2_rn(bf(kq[i]), bf(w3));
                    a = __hadd2_rn(a, __hmul2_rn(bf(kq[i + 1]), bf(w2)));
                    a = __hadd2_rn(a, __hmul2_rn(bf(kq[i + 2]), bf(w1)));
                    a = __hadd2_rn(a, __hmul2_rn(bf(kq[i + 3]), bf(w0)));
                    a = __hmul2_rn(a, bf(vq[i]));
                    u[i] = *reinterpret_cast<uint32_t*>(&a);
                }
                #pragma unroll
                for (int j = 0; j < 2; j++) {
                    const int e = (j + lane) & 1;
                    const uint32_t sel = e ? 0x7632 : 0x5410;
                    uint4 o;
                    o.x = __byte_perm(u[7], u[6], sel); o.y = __byte_perm(u[5], u[4], sel); o.z = __byte_perm(u[3], u[2], sel); o.w = __byte_perm(u[1], u[0], sel);
                    sts128(sb + OFF_UST + ct * 128 + p * 64 + e * 32 + g * 16, o);
                }
                if (qd == 3) {
                    fence_proxy_async_smem();
                    __syncwarp();
                    if (lane == 0) { mbar_arrive(bars + 8 * B_KVFREE); mbar_arrive(bars + 8 * B_USIG); }
                }
            }
            }
            TICK(2);
        }
        int it = 0;
        {
            float acc[96];
            #pragma unroll 1
            for (int kb = 0; kb < 10; kb++, it++) {
                int s = it & 3;
                mbar_wait(bars + 8 * (B_FULL + s), (it >> 2) & 1);
                uint32_t st = sb + s * STAGE_BYTES;
                uint64_t da = make_desc(st + wgc * 8192, 16, 1024, 1);
                uint64_t db = make_desc(st + 16384, 8192, 1024, 1);
                if (kb == 0) TICK(4);
                wg_fence();
                #pragma unroll
                for (int k = 0; k < 4; k++) wgmma_ss_tb_n192(acc, da + k * 2, db + k * 128, (kb | k) ? 1 : 0);
                wg_commit();
                if (kb > 0) {
                    wg_wait<1>();
                    if (kb - 1 < 8 && lane == 0) mbar_arrive(bars + 8 * (B_EMPTY + ((it - 1) & 3)));
                }
                if (kb == 9) {
                    mbar_wait(bars + 8 * B_HFULL, 0);
                    #pragma unroll
                    for (int ch = 0; ch < 5; ch++) {
                        uint32_t b0 = sb + OFF_HC + ch * HC_PITCH + 16;
                        uint4 a = lds128(b0 + ct * 16);
                        uint32_t nx = (ct < 255) ? lds32(b0 + ct * 16 + 16) : 0u;
                        uint4 o;
                        o.x = __byte_perm(a.x, a.y, 0x5432); o.y = __byte_perm(a.y, a.z, 0x5432); o.z = __byte_perm(a.z, a.w, 0x5432); o.w = __byte_perm(a.w, nx, 0x5432);
                        sts128(sb + OFF_HC + ch * HC_PITCH + HC1_OFF + 16 + ct * 16, o);
                        if (ct == 0) {
                            uint32_t h0 = a.x & 0xffffu;
                            asm volatile("st.shared.b32 [%0], %1;" ::"r"(sb + OFF_HC + ch * HC_PITCH + HC1_OFF + 12), "r"(h0 << 16) : "memory");
                        }
                    }
                }
            }
            wg_wait<0>();
            TICK(5);
            bar_sync(1, 256);
            #pragma unroll
            for (int j = 0; j < 24; j += 2) {
                uint32_t r0 = pack_bf16(fmaxf(acc[4*j], 0.f), fmaxf(acc[4*j+1], 0.f));
                uint32_t r1 = pack_bf16(fmaxf(acc[4*j+2], 0.f), fmaxf(acc[4*j+3], 0.f));
                uint32_t r2 = pack_bf16(fmaxf(acc[4*j+4], 0.f), fmaxf(acc[4*j+5], 0.f));
                uint32_t r3 = pack_bf16(fmaxf(acc[4*j+6], 0.f), fmaxf(acc[4*j+7], 0.f));
                int mat = lane >> 3;
                int row = wgc * 64 + w4 * 16 + (lane & 7) + (mat & 1) * 8;
                int colg = j + (mat >> 1);
                int box = colg >> 3, cc = colg & 7;
                uint32_t addr = sb + box * 16384 + row * 128 + ((cc ^ (row & 7)) << 4);
                stmatrix_x4(addr, r0, r1, r2, r3);
            }
            fence_proxy_async_smem();
            __syncwarp();
            if (lane == 0) mbar_arrive(bars + 8 * B_HST);
            TICK(6);
        }

        {
            bar_sync(1, 256);
            mbar_wait(bars + 8 * B_UFULL, 0);
            TICK(7);
            const uint32_t ps = sb + (wgc ? 0 : STAGE_BYTES);
            const int par = (g4 + 1) & 1;
            #pragma unroll 1
            for (int ch = wgc; ch < 5; ch += 2) {
                const uint32_t hbase = sb + OFF_HC + ch * HC_PITCH;
                const float Dc = __bfloat162float(__ldg(P.ssm_D + cta * 5 + ch));
                const uint32_t pb = hbase + (par ? (HC1_OFF + 16 - 2) : 16) + 2 * (16 * w4 + g4 - 7 + 2 * c4);
                uint32_t A[64];
                #pragma unroll
                for (int g2 = 0; g2 < 16; g2++) {
                    A[4*g2+0] = lds32(pb + 128 * (2*g2+1));
                    A[4*g2+1] = lds32(pb + 128 * (2*g2+1) + 16);
                    A[4*g2+2] = lds32(pb + 128 * (2*g2));
                    A[4*g2+3] = lds32(pb + 128 * (2*g2) + 16);
                }
                float acc[128];
                const uint64_t db = make_desc(sb + OFF_U + ch * U_PITCH + U_ZPAD - 128, 128, 128, 0);
                TICK(19 + 2 * ch);
                if (ch > 0) bar_sync(4 + wgc, 256);
                wg_fence();
                CONV_MMA_CHAIN(acc, A, db);
                wg_commit();
                if (ch < 4) bar_arrive(4 + (wgc ^ 1), 256);
                wg_wait<0>();
                TICK(20 + 2 * ch);
                if (ch < 2) {
                    mbar_wait(bars + 8 * B_STGFREE, 0);
                    if (lane == 0) mbar_arrive(bars + 8 * (B_EMPTY + wgc));
                }
                {
                    float got[32];
                    #pragma unroll
                    for (int j = 0; j < 32; j++) {
                        float send = (c4 == 3) ? (j ? acc[4*j-1] : 0.f) : acc[4*j+3];
                        got[j] = __shfl_sync(0xffffffffu, send, (lane & ~3) | ((c4 + 3) & 3));
                    }
                    const uint32_t dst = ps + ((w4 * 8 + g4) * 264 + 2 * w4 + 2 * c4) * 4;
                    #pragma unroll
                    for (int j = 0; j < 32; j++) {
                        float p0 = acc[4*j] + got[j], p1 = acc[4*j+1] + acc[4*j+2];
                        asm volatile("st.shared.v2.f32 [%0], {%1, %2};" ::"r"(dst + j * 32), "f"(p0), "f"(p1) : "memory");
                    }
                }
                if (ch == 0) TICK(21);
                bar_sync(2 + wgc, 128);
                if (ch == 0) TICK(22);
                const int t128 = ct & 127;
                uint4 o[2];
                #pragma unroll
                for (int hh = 0; hh < 2; hh++) {
                    int a = t128 + 128 * hh;
                    uint4 ub = lds128(sb + OFF_U + ch * U_PITCH + U_ZPAD + a * 16);
                    uint32_t uw[4] = {ub.x, ub.y, ub.z, ub.w};
                    float y2[8];
                    #pragma unroll
                    for (int b = 0; b < 8; b++) {
                        uint32_t ad = ps + (b * 264 + a) * 4;
                        float y = __uint_as_float(lds32(ad));
                        float y1 = __uint_as_float(lds32(ad + 8 * 264 * 4));
                        float y2_ = __uint_as_float(lds32(ad + 16 * 264 * 4));
                        float y3 = __uint_as_float(lds32(ad + 24 * 264 * 4));
                        if (hh == 0) { if (a < 2) y1 = 0.f; if (a < 4) y2_ = 0.f; if (a < 6) y3 = 0.f; }
                        float yy = (y + y1) + (y2_ + y3);
                        int e = 7 - b;
                        float uu = (e & 1) ? bf_hi(uw[e >> 1]) : bf_lo(uw[e >> 1]);
                        y2[b] = bf16r(bf16r(yy) + bf16r(uu * Dc));
                    }
                    o[hh].x = pack_bf16(y2[0], y2[1]); o[hh].y = pack_bf16(y2[2], y2[3]); o[hh].z = pack_bf16(y2[4], y2[5]); o[hh].w = pack_bf16(y2[6], y2[7]);
                }
                #pragma unroll
                for (int hh = 0; hh < 2; hh++) *reinterpret_cast<uint4*>(g_y2T + (size_t)(cta * 5 + ch) * S_ + 8 * (t128 + 128 * hh)) = o[hh];
                if (ch == 0) TICK(25);
                bar_sync(2 + wgc, 128);
                if (ch == 0) TICK(26);
            }
            __syncwarp();
            if (lane == 0) { mbar_arrive(bars + 8 * B_YSIG); mbar_arrive(bars + 8 * (B_EMPTY + (wgc ^ 1))); }
            TICK(8);
            asm volatile("barrier.cluster.wait.acquire.aligned;" ::: "memory");
            if (lane == 0) {
                uint32_t peer_bar;
                asm volatile("mapa.shared::cluster.u32 %0, %1, %2;" : "=r"(peer_bar) : "r"(bars + 8 * B_XFREE), "r"(kh ^ 1));
                mbar_arrive_remote(peer_bar);
            }
        }

        {
            float acc[80];
            for (int kb = 0; kb < 12; kb++, it++) {
                int s = it & 3;
                mbar_wait(bars + 8 * (B_FULL + s), (it >> 2) & 1);
                uint32_t st = sb + s * STAGE_BYTES;
                uint64_t da = make_desc(st + wgc * 8192, 16, 1024, 1);
                uint64_t db = make_desc(st + 16384, 4096, 512, 2);
                if (kb == 0) TICK(9);
                wg_fence();
                #pragma unroll
                for (int k = 0; k < 4; k++) wgmma_ss_tb_n160(acc, da + k * 2, db + k * 64, (kb | k) ? 1 : 0);
                wg_commit();
                if (kb > 0) {
                    wg_wait<1>();
                    if (lane == 0) mbar_arrive(bars + 8 * (B_EMPTY + ((it - 1) & 3)));
                }
            }
            wg_wait<0>();
            TICK(10);
            mbar_wait_cluster(bars + 8 * B_XFREE, 0);
            {
                uint32_t xb_peer, bar_peer;
                asm volatile("mapa.shared::cluster.u32 %0, %1, %2;" : "=r"(xb_peer) : "r"(sb + OFF_XB), "r"(kh ^ 1));
                asm volatile("mapa.shared::cluster.u32 %0, %1, %2;" : "=r"(bar_peer) : "r"(bars + 8 * B_XFULL), "r"(kh ^ 1));
                #pragma unroll
                for (int i = 0; i < 10; i++) {
                    float v0 = kh ? acc[4*i] : acc[40+4*i], v1 = kh ? acc[4*i+1] : acc[40+4*i+1], v2 = kh ? acc[4*i+2] : acc[40+4*i+2], v3 = kh ? acc[4*i+3] : acc[40+4*i+3];
                    asm volatile("st.shared::cluster.v4.f32 [%0], {%1,%2,%3,%4};" ::"r"(xb_peer + (i * 256 + ct) * 16), "f"(v0), "f"(v1), "f"(v2), "f"(v3) : "memory");
                }
                __syncwarp();
                if (lane == 0) mbar_arrive_remote(bar_peer);
            }
            const uint32_t ownb = sb + ((it + 1) & 3) * STAGE_BYTES;
            bar_sync(1, 256);
            #pragma unroll
            for (int i = 0; i < 10; i++) {
                float v0 = kh ? acc[40+4*i] : acc[4*i], v1 = kh ? acc[40+4*i+1] : acc[4*i+1], v2 = kh ? acc[40+4*i+2] : acc[4*i+2], v3 = kh ? acc[40+4*i+3] : acc[4*i+3];
                asm volatile("st.shared.v4.f32 [%0], {%1,%2,%3,%4};" ::"r"(ownb + (i * 256 + ct) * 16), "f"(v0), "f"(v1), "f"(v2), "f"(v3) : "memory");
            }
            const int col0 = cb * 160 + kh * 80;
            const uint32_t xt = sb + (it & 3) * STAGE_BYTES;
            mbar_wait(bars + 8 * (B_FULL + (it & 3)), (it >> 2) & 1);
            mbar_wait(bars + 8 * B_YFULL, 0);
            mbar_wait_cluster(bars + 8 * B_XFULL, 0);
            TICK(11);
            #pragma unroll 1
            for (int i5 = 0; i5 < 10; i5 += 5) {
                uint4 r[5], ro[5];
                uint32_t xw[5][2], xnw[5][2], y0[5][2], y1[5][2];
                #pragma unroll
                for (int ii = 0; ii < 5; ii++) {
                    const int i = i5 + ii;
                    r[ii] = lds128(sb + OFF_XB + (i * 256 + ct) * 16);
                    ro[ii] = lds128(ownb + (i * 256 + ct) * 16);
                    #pragma unroll
                    for (int hf = 0; hf < 2; hf++) {
                        const int rl = wgc * 64 + w4 * 16 + g4 + hf * 8;
                        const int cl = 8 * i + 2 * c4;
                        xw[ii][hf] = lds32(xt + rl * 160 + cl * 2);
                        xnw[ii][hf] = lds32(xt + 20480 + rl * 160 + cl * 2);
                        const int box = rl >> 6, tl = rl & 63;
                        const uint32_t yb = sb + OFF_YT + box * 10240 + ((tl & 7) << 1);
                        asm volatile("ld.shared.u16 %0, [%1];" : "=r"(y0[ii][hf]) : "r"(yb + cl * 128 + (((tl >> 3) ^ (cl & 7)) << 4)));
                        asm volatile("ld.shared.u16 %0, [%1];" : "=r"(y1[ii][hf]) : "r"(yb + (cl + 1) * 128 + (((tl >> 3) ^ ((cl + 1) & 7)) << 4)));
                    }
                }
                uint32_t res[5][2];
                #pragma unroll
                for (int ii = 0; ii < 5; ii++) {
                    float z[4];
                    z[0] = __uint_as_float(ro[ii].x) + __uint_as_float(r[ii].x);
                    z[1] = __uint_as_float(ro[ii].y) + __uint_as_float(r[ii].y);
                    z[2] = __uint_as_float(ro[ii].z) + __uint_as_float(r[ii].z);
                    z[3] = __uint_as_float(ro[ii].w) + __uint_as_float(r[ii].w);
                    #pragma unroll
                    for (int hf = 0; hf < 2; hf++) {
                        const uint32_t yw = __byte_perm(y0[ii][hf], y1[ii][hf], 0x5410);
                        const uint32_t zw = pack_bf16(z[2 * hf], z[2 * hf + 1]);
                        const float z0 = bf_lo(zw), z1 = bf_hi(zw);
                        const uint32_t gw = pack_bf16(__fdividef(z0, 1.0f + __expf(-z0)), __fdividef(z1, 1.0f + __expf(-z1)));
                        __nv_bfloat162 sv = __hmul2_rn(*reinterpret_cast<const __nv_bfloat162*>(&xnw[ii][hf]), *reinterpret_cast<const __nv_bfloat162*>(&yw));
                        sv = __hmul2_rn(sv, *reinterpret_cast<const __nv_bfloat162*>(&gw));
                        sv = __hadd2_rn(*reinterpret_cast<const __nv_bfloat162*>(&xw[ii][hf]), sv);
                        res[ii][hf] = *reinterpret_cast<uint32_t*>(&sv);
                    }
                }
                #pragma unroll
                for (int ii = 0; ii < 5; ii++) {
                    #pragma unroll
                    for (int hf = 0; hf < 2; hf++) {
                        const int rl = wgc * 64 + w4 * 16 + g4 + hf * 8;
                        const int cl = 8 * (i5 + ii) + 2 * c4;
                        asm volatile("st.shared.b32 [%0], %1;" ::"r"(xt + rl * 160 + cl * 2), "r"(res[ii][hf]) : "memory");
                    }
                }
            }
            fence_proxy_async_smem();
            bar_sync(1, 256);
            if (ct == 0) {
                tma_store_2d(&tm_out, xt, col0, rb * 128);
                bulk_commit();
                asm volatile("cp.async.bulk.wait_group.read 0;" ::: "memory");
            }
        }
    }
    if (wg == 0) asm volatile("barrier.cluster.wait.acquire.aligned;" ::: "memory");
    __syncthreads();
    if (tid == 0) {
        __threadfence();
        unsigned t = atomicAdd(&g_flags[FL_TICKET], 1u);
        if (t == NCTA - 1) { g_flags[FL_TICKET] = 0; __threadfence(); st_release(&g_flags[FL_EPOCH], ep1); }
    }
}

typedef CUresult (*EncFn)(CUtensorMap*, CUtensorMapDataType, cuuint32_t, void*, const cuuint64_t*, const cuuint64_t*, const cuuint32_t*, const cuuint32_t*,
                          CUtensorMapInterleave, CUtensorMapSwizzle, CUtensorMapL2promotion, CUtensorMapFloatOOBfill);

bool make_map_2d(EncFn enc, CUtensorMap* m, const void* ptr, uint64_t inner, uint64_t outer, uint32_t box_in, uint32_t box_out, CUtensorMapSwizzle swz) {
    cuuint64_t dims[2] = {inner, outer};
    cuuint64_t strides[1] = {inner * 2};
    cuuint32_t box[2] = {box_in, box_out};
    cuuint32_t es[2] = {1, 1};
    return enc(m, CU_TENSOR_MAP_DATA_TYPE_BFLOAT16, 2, const_cast<void*>(ptr), dims, strides, box, es, CU_TENSOR_MAP_INTERLEAVE_NONE, swz,
               CU_TENSOR_MAP_L2_PROMOTION_L2_128B, CU_TENSOR_MAP_FLOAT_OOB_FILL_NONE) == CUDA_SUCCESS;
}

}

extern "C" void kernel_launch(void* const* d_in, const int* in_sizes, int n_in, void* d_out, int out_size) {
    static EncFn enc = nullptr;
    if (!enc) {
        void* fn = nullptr; cudaDriverEntryPointQueryResult q;
        cudaGetDriverEntryPoint("cuTensorMapEncodeTiled", &fn, cudaEnableDefault, &q);
        enc = (EncFn)fn;
        cudaFuncSetAttribute(fused_kernel, cudaFuncAttributeMaxDynamicSharedMemorySize, SMEM_BYTES);
    }
    KParams P;
    P.x = (const __nv_bfloat16*)d_in[0]; P.k = (const __nv_bfloat16*)d_in[1]; P.v = (const __nv_bfloat16*)d_in[2];
    P.shift_k = (const __nv_bfloat16*)d_in[3]; P.ssm_k = (const __nv_bfloat16*)d_in[4]; P.ssm_D = (const __nv_bfloat16*)d_in[5];
    P.w1 = (const __nv_bfloat16*)d_in[7]; P.w2 = (const __nv_bfloat16*)d_in[8];
    P.out = (__nv_bfloat16*)d_out;
    void *p_xn, *p_h, *p_y2T;
    cudaGetSymbolAddress(&p_xn, g_xn); cudaGetSymbolAddress(&p_h, g_h); cudaGetSymbolAddress(&p_y2T, g_y2T);
    CUtensorMap tm_xn, tm_w1, tm_h, tm_w2, tm_y2T, tm_xe, tm_xne, tm_uT, tm_out;
    make_map_2d(enc, &tm_out, P.out, D_, S_, 80, 128, CU_TENSOR_MAP_SWIZZLE_NONE);
    void* p_uT; cudaGetSymbolAddress(&p_uT, g_uT);
    make_map_2d(enc, &tm_uT, p_uT, S_, D_, 16, 128, CU_TENSOR_MAP_SWIZZLE_NONE);
    make_map_2d(enc, &tm_xn, p_xn, D_, S_, 64, 128, CU_TENSOR_MAP_SWIZZLE_128B);
    make_map_2d(enc, &tm_w1, P.w1, DFF_, D_, 64, 64, CU_TENSOR_MAP_SWIZZLE_128B);
    make_map_2d(enc, &tm_h, p_h, DFF_, S_, 64, 128, CU_TENSOR_MAP_SWIZZLE_128B);
    make_map_2d(enc, &tm_w2, P.w2, D_, DFF_, 32, 64, CU_TENSOR_MAP_SWIZZLE_64B);
    make_map_2d(enc, &tm_y2T, p_y2T, S_, D_, 64, 80, CU_TENSOR_MAP_SWIZZLE_128B);
    make_map_2d(enc, &tm_xe, P.x, D_, S_, 80, 128, CU_TENSOR_MAP_SWIZZLE_NONE);
    make_map_2d(enc, &tm_xne, p_xn, D_, S_, 80, 128, CU_TENSOR_MAP_SWIZZLE_NONE);

    cudaLaunchConfig_t cfg = {};
    cfg.gridDim = dim3(NCTA); cfg.blockDim = dim3(NTHREADS); cfg.dynamicSmemBytes = SMEM_BYTES; cfg.stream = cudaStreamPerThread;
    cudaLaunchAttribute at[1];
    at[0].id = cudaLaunchAttributeClusterDimension; at[0].val.clusterDim.x = 2; at[0].val.clusterDim.y = 1; at[0].val.clusterDim.z = 1;
    cfg.attrs = at; cfg.numAttrs = 1;
    cudaLaunchKernelEx(&cfg, fused_kernel, tm_xn, tm_w1, tm_h, tm_w2, tm_y2T, tm_xe, tm_xne, tm_uT, tm_out, P);
}
```
